```python
import torch

def _softmax(x, axis=-1):
    return torch.softmax(x, dim=axis)

def _gelu(x):
    return torch.nn.functional.gelu(x, approximate='tanh')

def _silu(x):
    return torch.nn.functional.silu(x)

def _sigmoid(x):
    return torch.sigmoid(x)

def _layernorm(x, axis=-1, eps=1e-05):
    m = x.mean(dim=axis, keepdim=True)
    v = x.var(dim=axis, keepdim=True, unbiased=False)
    return (x - m) / torch.sqrt(v + eps)

def _scatter_add(tgt, idx, src, axis=0):
    return tgt.clone().index_add_(axis, idx, src)

def _segment_sum(src, seg, n):
    out = torch.zeros((n,) + src.shape[1:], dtype=src.dtype)
    return out.index_add_(0, seg, src)

def _pad(x, pw):
    flat = tuple((v for pair in reversed(pw) for v in pair))
    return torch.nn.functional.pad(x, flat)
kernel_name = 'adaLN_cond__gqa_block_cached__geglu_ffn__decode'

def setup_inputs():

    _w = lambda a: (lambda t: t.to(torch.bfloat16) if t.is_floating_point() else t)(torch.as_tensor(a))

    def _A_setup():
        B, Sq, D = (8, 1, 576)
        Hq, Hkv, Sk, Dh = (32, 16, 8192, 128)
        assert Hq % Hkv == 0, (Hq, Hkv)
        return {'x': _w((lambda *s: torch.randn(*s, dtype=torch.bfloat16) * 0.1)(B, Sq, D)), 'k_cache': _w((lambda *s: torch.randn(*s, dtype=torch.bfloat16) * 0.8)(B, Hkv, Sk, Dh)), 'v_cache': _w((lambda *s: torch.randn(*s, dtype=torch.bfloat16) * 0.8)(B, Hkv, Sk, Dh)), 'wq': _w((lambda *s: torch.randn(*s, dtype=torch.bfloat16) * 0.8)(D, Hq * Dh) * D ** (-0.5)), 'wo': _w((lambda *s: torch.randn(*s, dtype=torch.bfloat16) * 0.8)(Hq * Dh, D) * (Hq * Dh) ** (-0.5))}
    _A_in = _A_setup()

    def _B_setup():
        B, S, D, F = (8, 1, 576, 4608)
        return {'x': _w((lambda *s: torch.randn(*s, dtype=torch.bfloat16) * 0.1)(B, S, D)), 'w_gate': _w((lambda *s: torch.randn(*s, dtype=torch.bfloat16) * 0.1)(D, F)), 'w_up': _w((lambda *s: torch.randn(*s, dtype=torch.bfloat16) * 0.1)(D, F)), 'w_down': _w((lambda *s: torch.randn(*s, dtype=torch.bfloat16) * 0.1)(F, D))}
    _B_in = _B_setup()
    return {'A_x': _A_in['x'], 'A_k_cache': _A_in['k_cache'], 'A_v_cache': _A_in['v_cache'], 'A_wq': _A_in['wq'], 'A_wo': _A_in['wo'], 'B_x': _B_in['x'], 'B_w_gate': _B_in['w_gate'], 'B_w_up': _B_in['w_up'], 'B_w_down': _B_in['w_down'], 'c': _w((lambda *s: torch.randn(*s, dtype=torch.bfloat16) * 0.4)(8, 576) * 8.0), 'w_mod': _w((lambda *s: torch.randn(*s, dtype=torch.bfloat16) * 0.4)(576, 6 * 576) * 576 ** (-0.5) * 8.0)}

def reference(A_x, A_k_cache, A_v_cache, A_wq, A_wo, B_x, B_w_gate, B_w_up, B_w_down, c, w_mod):

    def _A_ref(x, k_cache, v_cache, wq, wo):
        B, Sq, D = x.shape
        Hq, Dh = (32, 128)
        Hkv = k_cache.shape[1]
        rep = Hq // Hkv
        q = (lambda x, *d: x.permute(*d))((x @ wq).reshape(B, Sq, Hq, Dh), 0, 2, 1, 3)
        k = (lambda x, n, axis: torch.repeat_interleave(x, n, dim=axis))(k_cache, rep, axis=1)
        v = (lambda x, n, axis: torch.repeat_interleave(x, n, dim=axis))(v_cache, rep, axis=1)
        scores = torch.einsum('bhqd,bhkd->bhqk', q, k) * Dh ** (-0.5)
        p = _softmax(scores, axis=-1)
        o = torch.einsum('bhqk,bhkd->bhqd', p, v)
        return (lambda x, *d: x.permute(*d))(o, 0, 2, 1, 3).reshape(B, Sq, Hq * Dh) @ wo

    def _B_ref(x, w_gate, w_up, w_down):
        return _gelu(x @ w_gate) * (x @ w_up) @ w_down
    x = A_x
    mod = (_silu(c) @ w_mod).reshape(c.shape[0], 6, 1, -1)
    sa, ca, ga, sb, cb, gb = (mod[:, 0].clone(), mod[:, 1].clone(), mod[:, 2].clone(), mod[:, 3].clone(), mod[:, 4].clone(), mod[:, 5].clone())
    h = _layernorm(x, axis=-1) * (1 + ca) + sa
    x = x + ga * _A_ref(h, A_k_cache, A_v_cache, A_wq, A_wo)
    h = _layernorm(x, axis=-1) * (1 + cb) + sb
    x = x + gb * _B_ref(h, B_w_gate, B_w_up, B_w_down)
    return x
```

```cpp
#include <cuda_runtime.h>
#include <cuda_bf16.h>
#include <cuda.h>
#include <stdint.h>

namespace {

constexpr int NB = 8, DM = 576, SK = 8192, FF = 4608;
constexpr int NSLAB = 128;
constexpr int UPS = 256;
constexpr int NS = 12;
constexpr int SLOT = 16384;
constexpr int NCW = 8;
constexpr int NTHREADS = NCW * 32 + 32;
constexpr int NWORK = 128;
constexpr int NMODCTA = 108;
constexpr int NMODCRIT = 36;

constexpr int S1 = 102, S2 = 122;
constexpr int C1 = 32, C2 = 8, C3 = 1;
constexpr int N1 = S1 * (UPS / C1);
constexpr int N2 = (S2 - S1) * (UPS / C2);
constexpr int N3 = (NSLAB - S2) * (UPS / C3);
constexpr int NITEMS = N1 + N2 + N3;
constexpr int NPART = N1 + N2 + (NSLAB - S2) * UPS;
static_assert(S2 >= 112, "region 3 must stay inside the last batch");
static_assert(UPS / C2 <= 32 && UPS / C1 <= 32, "combine assumes <= 32 partials outside region 3");

constexpr int SM_MERGE = NS * SLOT;
constexpr int MERGE_W = 264;
constexpr int SM_AUX = SM_MERGE + 2 * NCW * MERGE_W * 4;
constexpr int SM_BAR = SM_AUX + 16384;
constexpr int SM_TOTAL = SM_BAR + 1024;
constexpr int INP = 584;

constexpr float SCALE_LOG2 = 0.08838834764831845f * 1.4426950408889634f;

__device__ float g_partO[(size_t)NPART * 256];
__device__ float2 g_partML[(size_t)NPART * 2];
__device__ __nv_bfloat16 g_mod[NB * 6 * DM];
__device__ __nv_bfloat16 g_q[NB * 4096];
__device__ float g_acc1[NB * DM];
__device__ float g_acc2[NB * DM];
__device__ unsigned g_ctr[8 * 32];
enum { CT_ITEM = 0, CT_MOD = 32, CT_Q = 64, CT_A = 96, CT_B = 128, CT_C = 160 };

__device__ __forceinline__ uint32_t smem_u32(const void* p) { return (uint32_t)__cvta_generic_to_shared(p); }
__device__ __forceinline__ void mbar_init(uint32_t bar, uint32_t cnt) {
    asm volatile("mbarrier.init.shared::cta.b64 [%0], %1;" ::"r"(bar), "r"(cnt));
}
__device__ __forceinline__ void mbar_expect_tx(uint32_t bar, uint32_t bytes) {
    asm volatile("mbarrier.arrive.expect_tx.shared::cta.b64 _, [%0], %1;" ::"r"(bar), "r"(bytes) : "memory");
}
__device__ __forceinline__ void mbar_arrive(uint32_t bar) {
    asm volatile("mbarrier.arrive.shared::cta.b64 _, [%0];" ::"r"(bar) : "memory");
}
__device__ __forceinline__ bool mbar_try(uint32_t bar, uint32_t parity) {
    uint32_t ok;
    asm volatile("{\n.reg .pred p;\nmbarrier.try_wait.parity.shared::cta.b64 p, [%1], %2;\nselp.u32 %0, 1, 0, p;\n}"
                 : "=r"(ok) : "r"(bar), "r"(parity) : "memory");
    return ok != 0;
}
constexpr long long SPIN_LIMIT = 2000000000LL;
__device__ __forceinline__ void mbar_wait(uint32_t bar, uint32_t parity) {
    if (mbar_try(bar, parity)) return;
    const long long t0 = clock64();
    while (!mbar_try(bar, parity)) {
        if (clock64() - t0 > SPIN_LIMIT) __trap();
    }
}
__device__ __forceinline__ void bulk_load(uint32_t dst, const void* src, uint32_t bytes, uint32_t bar) {
    asm volatile("cp.async.bulk.shared::cluster.global.mbarrier::complete_tx::bytes [%0], [%1], %2, [%3];"
                 ::"r"(dst), "l"(src), "r"(bytes), "r"(bar) : "memory");
}
__device__ __forceinline__ void tma2d(uint32_t dst, const CUtensorMap* map, int c0, int c1, uint32_t bar) {
    asm volatile("cp.async.bulk.tensor.2d.shared::cluster.global.mbarrier::complete_tx::bytes [%0], [%1, {%3, %4}], [%2];"
                 ::"r"(dst), "l"((uint64_t)map), "r"(bar), "r"(c0), "r"(c1) : "memory");
}
__device__ __forceinline__ void ldsm4(uint32_t addr, uint32_t& r0, uint32_t& r1, uint32_t& r2, uint32_t& r3) {
    asm volatile("ldmatrix.sync.aligned.m8n8.x4.shared.b16 {%0,%1,%2,%3}, [%4];"
                 : "=r"(r0), "=r"(r1), "=r"(r2), "=r"(r3) : "r"(addr) : "memory");
}
__device__ __forceinline__ void ldsm4t(uint32_t addr, uint32_t& r0, uint32_t& r1, uint32_t& r2, uint32_t& r3) {
    asm volatile("ldmatrix.sync.aligned.m8n8.x4.trans.shared.b16 {%0,%1,%2,%3}, [%4];"
                 : "=r"(r0), "=r"(r1), "=r"(r2), "=r"(r3) : "r"(addr) : "memory");
}
__device__ __forceinline__ void mma16816(float* c, uint32_t a0, uint32_t a1, uint32_t a2, uint32_t a3, uint32_t b0,
                                         uint32_t b1) {
    asm volatile("mma.sync.aligned.m16n8k16.row.col.f32.bf16.bf16.f32 {%0,%1,%2,%3}, {%4,%5,%6,%7}, {%8,%9}, {%0,%1,%2,%3};"
                 : "+f"(c[0]), "+f"(c[1]), "+f"(c[2]), "+f"(c[3])
                 : "r"(a0), "r"(a1), "r"(a2), "r"(a3), "r"(b0), "r"(b1));
}
__device__ __forceinline__ uint32_t pack_bf16(float lo, float hi) {
    uint32_t r;
    asm("cvt.rn.bf16x2.f32 %0, %1, %2;" : "=r"(r) : "f"(hi), "f"(lo));
    return r;
}
__device__ __forceinline__ float bf_lo(uint32_t v) { return __uint_as_float(v << 16); }
__device__ __forceinline__ float bf_hi(uint32_t v) { return __uint_as_float(v & 0xffff0000u); }
__device__ __forceinline__ float ex2(float x) {
    float r;
    asm("ex2.approx.ftz.f32 %0, %1;" : "=f"(r) : "f"(x));
    return r;
}
__device__ __forceinline__ void consumer_bar() { asm volatile("bar.sync 1, 256;" ::: "memory"); }
__device__ __forceinline__ void red_release(unsigned* p) {
    asm volatile("red.release.gpu.global.add.u32 [%0], 1;" ::"l"(p) : "memory");
}
__device__ __forceinline__ unsigned ld_acquire(const unsigned* p) {
    unsigned v;
    asm volatile("ld.acquire.gpu.global.u32 %0, [%1];" : "=r"(v) : "l"(p) : "memory");
    return v;
}
__device__ __forceinline__ void spin_until(const unsigned* p, unsigned target) {
    if (ld_acquire(p) >= target) return;
    const long long t0 = clock64();
    while (ld_acquire(p) < target) {
        if (clock64() - t0 > SPIN_LIMIT) __trap();
    }
}
__device__ __forceinline__ void red_add_f32(float* p, float v) {
    asm volatile("red.relaxed.gpu.global.add.f32 [%0], %1;" ::"l"(p), "f"(v) : "memory");
}
__device__ __forceinline__ void grid_arrive(unsigned* ctr, int tid) {
    __threadfence();
    consumer_bar();
    if (tid == 0) red_release(ctr);
}
__device__ __forceinline__ void grid_wait(const unsigned* ctr, unsigned target, int tid) {
    if (tid == 0) spin_until(ctr, target);
    consumer_bar();
}

struct Params {
    const __nv_bfloat16* x;
    const __nv_bfloat16* wo;
    const __nv_bfloat16* wdown;
    const __nv_bfloat16* c;
    __nv_bfloat16* out;
};

__device__ __forceinline__ uint64_t make_meta(uint32_t seq, int slab, int first, int last, int single, int pslot) {
    uint32_t lo = (seq & 0xFFFFFu) | ((uint32_t)slab << 20) | ((uint32_t)first << 27) | ((uint32_t)last << 28) |
                  ((uint32_t)single << 29);
    return (uint64_t)lo | ((uint64_t)(uint32_t)pslot << 32);
}

__device__ __forceinline__ float gemv32(uint32_t ring, int slot0, const __nv_bfloat16* s_in, float* s_red, int warp,
                                        int lane, int tid, int& col, int& batch) {
    const int g = lane >> 2, c = lane & 3;
    float acc[2][4] = {{0.f, 0.f, 0.f, 0.f}, {0.f, 0.f, 0.f, 0.f}};
    for (int s = warp; s < 36; s += 8) {
        const int box = s / 12, r0 = (s % 12) * 16;
        const uint32_t base = ring + (slot0 + box) * SLOT;
        const int row = r0 + (lane & 7) + ((lane >> 4) & 1) * 8;
        const uint32_t b0 = *(const uint32_t*)(s_in + g * INP + s * 16 + 2 * c);
        const uint32_t b1 = *(const uint32_t*)(s_in + g * INP + s * 16 + 2 * c + 8);
#pragma unroll
        for (int mt = 0; mt < 2; mt++) {
            const int chunk = 2 * mt + ((lane >> 3) & 1);
            uint32_t a0, a1, a2, a3;
            ldsm4t(base + row * 64 + ((chunk ^ ((row >> 1) & 3)) << 4), a0, a1, a2, a3);
            mma16816(acc[mt], a0, a1, a2, a3, b0, b1);
        }
    }
#pragma unroll
    for (int mt = 0; mt < 2; mt++)
#pragma unroll
        for (int i = 0; i < 4; i++) s_red[warp * 256 + (mt * 4 + i) * 32 + lane] = acc[mt][i];
    consumer_bar();
    float v = 0.f;
#pragma unroll
    for (int w = 0; w < 8; w++) v += s_red[w * 256 + tid];
    const int mt = tid >> 7, i = (tid >> 5) & 3, l = tid & 31;
    col = 16 * mt + (l >> 2) + 8 * (i >> 1);
    batch = 2 * (l & 3) + (i & 1);
    return v;
}

__global__ void __launch_bounds__(NTHREADS, 1)
fused_kernel(const __grid_constant__ CUtensorMap mapK, const __grid_constant__ CUtensorMap mapV,
             const __grid_constant__ CUtensorMap mapMod, const __grid_constant__ CUtensorMap mapQ,
             const __grid_constant__ CUtensorMap mapG, const __grid_constant__ CUtensorMap mapU, const Params p) {
    extern __shared__ __align__(1024) unsigned char smem[];
    const uint32_t ring = smem_u32(smem);
    uint64_t* s_full = (uint64_t*)(smem + SM_BAR);
    uint64_t* s_empty = s_full + NS;
    volatile uint64_t* s_meta = (volatile uint64_t*)(s_empty + NS);
    volatile uint32_t* s_end = (volatile uint32_t*)(s_meta + NS);
    volatile uint32_t* s_flag = s_end + 1;
    const uint32_t full0 = smem_u32(s_full), empty0 = smem_u32(s_empty);

    const int tid = threadIdx.x, warp = tid >> 5, lane = tid & 31;
    const int cta = blockIdx.x, ncta = gridDim.x;

    if (tid == 0) {
        for (int s = 0; s < NS; s++) {
            mbar_init(full0 + 8 * s, 1);
            mbar_init(empty0 + 8 * s, 1);
            s_meta[s] = 0xFFFFFull;
        }
        *s_end = 0xFFFFFFFFu;
        asm volatile("fence.mbarrier_init.release.cluster;" ::: "memory");
    }
    __syncthreads();

    if (warp == NCW) {
        if (lane == 0) {
            for (int i = 0; i < 3; i++) {
                if (cta < NMODCTA) {
                    mbar_expect_tx(full0 + 8 * i, 192 * 64);
                    tma2d(ring + i * SLOT, &mapMod, cta * 32, i * 192, full0 + 8 * i);
                } else mbar_arrive(full0 + 8 * i);
            }
            for (int i = 0; i < 3; i++) {
                if (cta < NWORK) {
                    mbar_expect_tx(full0 + 8 * (3 + i), 192 * 64);
                    tma2d(ring + (3 + i) * SLOT, &mapQ, cta * 32, i * 192, full0 + 8 * (3 + i));
                } else mbar_arrive(full0 + 8 * (3 + i));
            }
            uint32_t seq = 6;
            int slot = 6;
            uint32_t eph = 1;
            int item = cta;
            while (item < NITEMS) {
                int unit0, n, single, pslot;
                if (item < N1) { unit0 = item * C1; n = C1; single = 0; pslot = item; }
                else if (item < N1 + N2) { unit0 = S1 * UPS + (item - N1) * C2; n = C2; single = 0; pslot = item; }
                else { unit0 = S2 * UPS + (item - N1 - N2) * C3; n = C3; single = 1; pslot = N1 + N2 + (item - N1 - N2) * C3; }
                const int slab = unit0 / UPS;
                int next = 0;
                const int pf = n > 3 ? n - 3 : 0;
                for (int u = 0; u < n; u++) {
                    if (u == pf) next = (int)atomicAdd(&g_ctr[CT_ITEM], 1u) + ncta;
                    mbar_wait(empty0 + 8 * slot, eph);
                    s_meta[slot] = make_meta(seq, slab, single || u < NCW, single || u + NCW >= n, single,
                                             single ? pslot + u : pslot);
                    const uint32_t fb = full0 + 8 * slot;
                    mbar_expect_tx(fb, SLOT);
                    tma2d(ring + slot * SLOT, &mapK, 0, (unit0 + u) * 64, fb);
                    tma2d(ring + slot * SLOT + 8192, &mapV, 0, (unit0 + u) * 64, fb);
                    seq++;
                    if (++slot == NS) { slot = 0; eph ^= 1; }
                }
                item = next;
            }
            *s_end = seq;
            if (cta < NWORK) {
                for (int i = 0; i < 12; i++) {
                    mbar_wait(empty0 + 8 * slot, eph);
                    const uint32_t fb = full0 + 8 * slot;
                    const uint32_t dst = ring + slot * SLOT;
                    if (i < 3) {
                        const int r0 = i * 11, nr = (i == 2) ? 10 : 11;
                        mbar_expect_tx(fb, nr * 1152);
                        for (int r = 0; r < nr; r++)
                            bulk_load(dst + r * 1168, p.wo + (size_t)(cta * 32 + r0 + r) * DM, 1152, fb);
                    } else if (i < 9) {
                        const int c0 = (cta * 36) & ~7;
                        mbar_expect_tx(fb, 192 * 80);
                        tma2d(dst, i < 6 ? &mapG : &mapU, c0, ((i - 3) % 3) * 192, fb);
                    } else {
                        const int r0 = (i - 9) * 12;
                        mbar_expect_tx(fb, 12 * 1152);
                        for (int r = 0; r < 12; r++)
                            bulk_load(dst + r * 1168, p.wdown + (size_t)(cta * 36 + r0 + r) * DM, 1152, fb);
                    }
                    if (++slot == NS) { slot = 0; eph ^= 1; }
                }
            }
        }
        return;
    }

    const int g = lane >> 2, c = lane & 3;
    __nv_bfloat16* s_in = (__nv_bfloat16*)(smem + SM_AUX);
    float* s_merge = (float*)(smem + SM_MERGE);

    float xn[18];
    {
        if (cta == ncta - 1) {
            for (int i = tid; i < NB * DM; i += 256) { g_acc1[i] = 0.f; g_acc2[i] = 0.f; }
        }
        for (int i = tid; i < NB * DM / 8; i += 256) {
            const uint4 v = *(const uint4*)(p.c + i * 8);
            const uint32_t w[4] = {v.x, v.y, v.z, v.w};
            uint32_t o[4];
#pragma unroll
            for (int j = 0; j < 4; j++) {
                const float a = bf_lo(w[j]), b = bf_hi(w[j]);
                o[j] = pack_bf16(a / (1.f + __expf(-a)), b / (1.f + __expf(-b)));
            }
            *(uint4*)(s_in + (i / 72) * INP + (i % 72) * 8) = make_uint4(o[0], o[1], o[2], o[3]);
        }
        float sum = 0.f;
#pragma unroll
        for (int i = 0; i < 9; i++) {
            const uint32_t v = *(const uint32_t*)(p.x + warp * DM + 2 * (lane + 32 * i));
            xn[2 * i] = bf_lo(v); xn[2 * i + 1] = bf_hi(v);
            sum += xn[2 * i] + xn[2 * i + 1];
        }
#pragma unroll
        for (int o = 16; o; o >>= 1) sum += __shfl_xor_sync(0xffffffffu, sum, o);
        const float mean = sum * (1.f / DM);
        float var = 0.f;
#pragma unroll
        for (int i = 0; i < 18; i++) { xn[i] -= mean; var += xn[i] * xn[i]; }
#pragma unroll
        for (int o = 16; o; o >>= 1) var += __shfl_xor_sync(0xffffffffu, var, o);
        const float rstd = 1.f / sqrtf(var * (1.f / DM) + 1e-5f);
#pragma unroll
        for (int i = 0; i < 18; i++) xn[i] *= rstd;
        consumer_bar();

        if (cta < NMODCTA) {
            for (int i = 0; i < 3; i++) mbar_wait(full0 + 8 * i, 0);
            int col, b;
            const float v = gemv32(ring, 0, s_in, s_merge, warp, lane, tid, col, b);
            g_mod[b * (6 * DM) + cta * 32 + col] = __float2bfloat16(v);
        }
        if (cta < NMODCRIT) grid_arrive(&g_ctr[CT_MOD], tid);
        else consumer_bar();
        if (tid == 0) for (int i = 0; i < 3; i++) mbar_arrive(empty0 + 8 * i);

        if (cta < NWORK) {
            grid_wait(&g_ctr[CT_MOD], NMODCRIT, tid);
            const __nv_bfloat16* md = g_mod + warp * (6 * DM);
#pragma unroll
            for (int i = 0; i < 9; i++) {
                const int col = 2 * (lane + 32 * i);
                const uint32_t sa = __ldcg((const uint32_t*)(md + col));
                const uint32_t ca = __ldcg((const uint32_t*)(md + DM + col));
                *(uint32_t*)(s_in + warp * INP + col) =
                    pack_bf16(xn[2 * i] * (1.f + bf_lo(ca)) + bf_lo(sa), xn[2 * i + 1] * (1.f + bf_hi(ca)) + bf_hi(sa));
            }
            consumer_bar();
            for (int i = 3; i < 6; i++) mbar_wait(full0 + 8 * i, 0);
            int col, b;
            const float v = gemv32(ring, 3, s_in, s_merge, warp, lane, tid, col, b);
            g_q[b * 4096 + cta * 32 + col] = __float2bfloat16(v);
            grid_arrive(&g_ctr[CT_Q], tid);
        }
        if (tid == 0) for (int i = 3; i < 6; i++) mbar_arrive(empty0 + 8 * i);
        grid_wait(&g_ctr[CT_Q], NWORK, tid);
    }

    {
        const int r = lane & 7, mi = lane >> 3;
        const bool valid = (g < 4) && ((g >> 1) == (c >> 1));
        uint32_t koff[2][2], voff[2][4];
#pragma unroll
        for (int ps = 0; ps < 2; ps++) {
            const int half = (r >> 2) ^ ps;
            const int x = 2 * (r & 3) + half;
#pragma unroll
            for (int i = 0; i < 2; i++) koff[ps][i] = (2 * r + half) * 128 + (((4 * i + mi) ^ x) << 4);
#pragma unroll
            for (int mt = 0; mt < 4; mt++)
                voff[ps][mt] = 8192 + (2 * (8 * (mi >> 1) + r) + half) * 128 + (((2 * mt + (mi & 1)) ^ x) << 4);
        }
        uint32_t qa[8][2];
        float acc[2][4][4];
        float m0 = -INFINITY, m1 = -INFINITY, lsum = 0.f;
        int mergebuf = 0;
        uint32_t seq = (warp >= 6) ? warp : warp + 8;
        bool done = false;
        while (true) {
            const int slot = seq % NS;
            const uint32_t par = (seq / NS) & 1;
            uint64_t meta;
            {
                uint32_t it = 0;
                while (true) {
                    meta = s_meta[slot];
                    if (((uint32_t)meta & 0xFFFFFu) == (seq & 0xFFFFFu)) break;
                    if (*s_end <= seq) { done = true; break; }
                    if (++it > (1u << 26)) __trap();
                }
            }
            if (done) break;
            const uint32_t mlo = (uint32_t)meta;
            const int slab = (mlo >> 20) & 127;
            const bool first = (mlo >> 27) & 1, last = (mlo >> 28) & 1, single = (mlo >> 29) & 1;
            const int pslot = (int)(meta >> 32);
            if (first) {
                const int b = slab >> 4, kvh = slab & 15;
                const uint32_t* qp = (const uint32_t*)(g_q + b * 4096 + kvh * 256 + (g & 1) * 128);
                const int u = (g >> 1) & 1;
#pragma unroll
                for (int s = 0; s < 8; s++) {
                    const int d0 = 64 * (u ^ (s >> 2)) + 16 * (s & 3) + 2 * c;
                    qa[s][0] = (g < 4) ? __ldcg(qp + (d0 >> 1)) : 0u;
                    qa[s][1] = (g < 4) ? __ldcg(qp + ((d0 + 8) >> 1)) : 0u;
                }
                m0 = m1 = -INFINITY; lsum = 0.f;
#pragma unroll
                for (int a = 0; a < 2; a++)
#pragma unroll
                    for (int b2 = 0; b2 < 4; b2++)
#pragma unroll
                        for (int i = 0; i < 4; i++) acc[a][b2][i] = 0.f;
            }
            mbar_wait(full0 + 8 * slot, par);
            const uint32_t base = ring + slot * SLOT;
            float s[4][4];
#pragma unroll
            for (int t = 0; t < 4; t++) {
                s[t][0] = s[t][1] = s[t][2] = s[t][3] = 0.f;
#pragma unroll
                for (int ps = 0; ps < 2; ps++)
#pragma unroll
                    for (int i = 0; i < 2; i++) {
                        uint32_t b0, b1, b2, b3;
                        ldsm4(base + t * 2048 + koff[ps][i], b0, b1, b2, b3);
                        mma16816(s[t], qa[ps * 4 + 2 * i][0], 0u, qa[ps * 4 + 2 * i][1], 0u, b0, b1);
                        mma16816(s[t], qa[ps * 4 + 2 * i + 1][0], 0u, qa[ps * 4 + 2 * i + 1][1], 0u, b2, b3);
                    }
            }
            float mx = -INFINITY;
#pragma unroll
            for (int t = 0; t < 4; t++) {
                s[t][0] = valid ? s[t][0] * SCALE_LOG2 : -INFINITY;
                s[t][1] = valid ? s[t][1] * SCALE_LOG2 : -INFINITY;
                mx = fmaxf(mx, fmaxf(s[t][0], s[t][1]));
            }
            mx = fmaxf(mx, __shfl_xor_sync(0xffffffffu, mx, 1));
            mx = fmaxf(mx, __shfl_xor_sync(0xffffffffu, mx, 10));
            const float mx0 = __shfl_sync(0xffffffffu, mx, 0), mx1 = __shfl_sync(0xffffffffu, mx, 4);
            if (mx0 > m0 || mx1 > m1) {
                const float n0 = fmaxf(m0, mx0), n1 = fmaxf(m1, mx1);
                const float a0 = ex2(m0 - n0), a1 = ex2(m1 - n1);
                m0 = n0; m1 = n1;
                lsum *= (g & 1) ? a1 : a0;
#pragma unroll
                for (int a = 0; a < 2; a++)
#pragma unroll
                    for (int b2 = 0; b2 < 4; b2++) {
                        acc[a][b2][0] *= a0; acc[a][b2][1] *= a1; acc[a][b2][2] *= a0; acc[a][b2][3] *= a1;
                    }
            }
            const float mh = (g & 1) ? m1 : m0;
            uint32_t pb[4];
#pragma unroll
            for (int t = 0; t < 4; t++) {
                const float p0 = ex2(s[t][0] - mh), p1 = ex2(s[t][1] - mh);
                lsum += p0 + p1;
                pb[t] = pack_bf16(p0, p1);
            }
#pragma unroll
            for (int kk = 0; kk < 2; kk++)
#pragma unroll
                for (int ps = 0; ps < 2; ps++)
#pragma unroll
                    for (int mt = 0; mt < 4; mt++) {
                        uint32_t a0, a1, a2, a3;
                        ldsm4t(base + kk * 4096 + voff[ps][mt], a0, a1, a2, a3);
                        mma16816(acc[ps][mt], a0, a1, a2, a3, pb[2 * kk], pb[2 * kk + 1]);
                    }
            __syncwarp();
            if (lane == 0) mbar_arrive(empty0 + 8 * slot);

            if (last) {
                float l = lsum;
                l += __shfl_xor_sync(0xffffffffu, l, 1);
                l += __shfl_xor_sync(0xffffffffu, l, 10);
                const float l0 = __shfl_sync(0xffffffffu, l, 0), l1 = __shfl_sync(0xffffffffu, l, 4);
                float res[4][4];
#pragma unroll
                for (int mt = 0; mt < 4; mt++)
#pragma unroll
                    for (int i = 0; i < 4; i++) res[mt][i] = acc[0][mt][i] + __shfl_xor_sync(0xffffffffu, acc[1][mt][i], 1);
                if (single) {
                    float* dst = g_partO + (size_t)pslot * 256;
                    if (c < 2) {
#pragma unroll
                        for (int mt = 0; mt < 4; mt++)
#pragma unroll
                            for (int i = 0; i < 4; i++)
                                dst[(i & 1) * 128 + 64 * c + 16 * mt + g + 8 * (i >> 1)] = res[mt][i];
                    }
                    if (lane == 0) { g_partML[pslot * 2] = make_float2(m0, l0); g_partML[pslot * 2 + 1] = make_float2(m1, l1); }
                } else {
                    float* dst = s_merge + (mergebuf * NCW + warp) * MERGE_W;
                    if (c < 2) {
#pragma unroll
                        for (int mt = 0; mt < 4; mt++)
#pragma unroll
                            for (int i = 0; i < 4; i++)
                                dst[(i & 1) * 128 + 64 * c + 16 * mt + g + 8 * (i >> 1)] = res[mt][i];
                    }
                    if (lane == 0) { dst[256] = m0; dst[257] = m1; dst[258] = l0; dst[259] = l1; }
                    consumer_bar();
                    const float* src = s_merge + mergebuf * NCW * MERGE_W;
                    const int h = tid >> 7;
                    float M = -INFINITY;
#pragma unroll
                    for (int w = 0; w < NCW; w++) M = fmaxf(M, src[w * MERGE_W + 256 + h]);
                    float o = 0.f, L = 0.f;
#pragma unroll
                    for (int w = 0; w < NCW; w++) {
                        const float sc = ex2(src[w * MERGE_W + 256 + h] - M);
                        o += sc * src[w * MERGE_W + tid];
                        L += sc * src[w * MERGE_W + 258 + h];
                    }
                    g_partO[(size_t)pslot * 256 + tid] = o;
                    if ((tid & 127) == 0) g_partML[pslot * 2 + h] = make_float2(M, L);
                    mergebuf ^= 1;
                }
            }
            seq += NCW;
        }
    }
    grid_arrive(&g_ctr[CT_A], tid);
    if (cta >= NWORK) return;

    const uint32_t seq_end = *s_end;
    auto wslot = [&](int i) -> uint32_t { return ring + ((seq_end + i) % NS) * SLOT; };
    auto wwait = [&](int i) { const uint32_t s = seq_end + i; mbar_wait(full0 + 8 * (s % NS), (s / NS) & 1); };

    grid_wait(&g_ctr[CT_A], ncta, tid);
    {
        const int hq = cta >> 2, kvh = hq >> 1, h = hq & 1, dq = (cta & 3) * 32;
        const int tg = tid >> 3, t8 = tid & 7;
        float4 ov[15];
        float2 ml[15];
#pragma unroll
        for (int rd = 0; rd < 15; rd++) {
            const int b = rd < 7 ? rd : 7;
            const int slab = b * 16 + kvh;
            int p0, np;
            if (slab < S1) { p0 = slab * (UPS / C1); np = UPS / C1; }
            else if (slab < S2) { p0 = N1 + (slab - S1) * (UPS / C2); np = UPS / C2; }
            else { p0 = N1 + N2 + (slab - S2) * UPS; np = UPS; }
            const int idx = tg + 32 * (rd < 7 ? 0 : rd - 7);
            if (idx < np) {
                ov[rd] = __ldcg((const float4*)(g_partO + (size_t)(p0 + idx) * 256 + h * 128 + dq + t8 * 4));
                ml[rd] = __ldcg(&g_partML[(p0 + idx) * 2 + h]);
            } else {
                ov[rd] = make_float4(0.f, 0.f, 0.f, 0.f);
                ml[rd] = make_float2(-INFINITY, 0.f);
            }
        }
        float* s_o = s_merge;
        float* s_ml = s_merge + 2048;
#pragma unroll
        for (int b = 0; b < 8; b++) {
            float M = ml[b].x;
            if (b == 7) {
#pragma unroll
                for (int rd = 8; rd < 15; rd++) M = fmaxf(M, ml[rd].x);
            }
            M = fmaxf(M, __shfl_xor_sync(0xffffffffu, M, 8));
            M = fmaxf(M, __shfl_xor_sync(0xffffffffu, M, 16));
            const float Ms = (M == -INFINITY) ? 0.f : M;
            float sc = ex2(ml[b].x - Ms);
            float4 a = make_float4(ov[b].x * sc, ov[b].y * sc, ov[b].z * sc, ov[b].w * sc);
            float L = ml[b].y * sc;
            if (b == 7) {
#pragma unroll
                for (int rd = 8; rd < 15; rd++) {
                    sc = ex2(ml[rd].x - Ms);
                    a.x += ov[rd].x * sc; a.y += ov[rd].y * sc; a.z += ov[rd].z * sc; a.w += ov[rd].w * sc;
                    L += ml[rd].y * sc;
                }
            }
#pragma unroll
            for (int o = 8; o <= 16; o <<= 1) {
                a.x += __shfl_xor_sync(0xffffffffu, a.x, o);
                a.y += __shfl_xor_sync(0xffffffffu, a.y, o);
                a.z += __shfl_xor_sync(0xffffffffu, a.z, o);
                a.w += __shfl_xor_sync(0xffffffffu, a.w, o);
                L += __shfl_xor_sync(0xffffffffu, L, o);
            }
            if (lane < 8) *(float4*)(s_o + (warp * 8 + b) * 32 + lane * 4) = a;
            if (lane == 0) { s_ml[(warp * 8 + b) * 2] = M; s_ml[(warp * 8 + b) * 2 + 1] = L; }
        }
        consumer_bar();
        __nv_bfloat16* s_ob = s_in;
        {
            const int b = tid >> 5, d = tid & 31;
            float M = -INFINITY;
#pragma unroll
            for (int w = 0; w < 8; w++) M = fmaxf(M, s_ml[(w * 8 + b) * 2]);
            float o = 0.f, L = 0.f;
#pragma unroll
            for (int w = 0; w < 8; w++) {
                const float sc = ex2(s_ml[(w * 8 + b) * 2] - M);
                o += sc * s_o[(w * 8 + b) * 32 + d];
                L += sc * s_ml[(w * 8 + b) * 2 + 1];
            }
            s_ob[b * 40 + d] = __float2bfloat16(o / L);
        }
        consumer_bar();
        for (int i = 0; i < 3; i++) wwait(i);
        uint32_t bq[2][2];
#pragma unroll
        for (int ks = 0; ks < 2; ks++) {
            bq[ks][0] = *(const uint32_t*)(s_ob + g * 40 + ks * 16 + 2 * c);
            bq[ks][1] = *(const uint32_t*)(s_ob + g * 40 + ks * 16 + 2 * c + 8);
        }
        uint32_t rowaddr[2];
#pragma unroll
        for (int ks = 0; ks < 2; ks++) {
            const int row = ks * 16 + (lane & 7) + ((lane >> 4) & 1) * 8;
            rowaddr[ks] = wslot(row / 11) + (row % 11) * 1168 + ((lane >> 3) & 1) * 16;
        }
        for (int mt = warp; mt < 36; mt += 8) {
            float a4[4] = {0.f, 0.f, 0.f, 0.f};
#pragma unroll
            for (int ks = 0; ks < 2; ks++) {
                uint32_t a0, a1, a2, a3;
                ldsm4t(rowaddr[ks] + mt * 32, a0, a1, a2, a3);
                mma16816(a4, a0, a1, a2, a3, bq[ks][0], bq[ks][1]);
            }
            float* dst = g_acc1 + (2 * c) * DM + mt * 16 + g;
            red_add_f32(dst, a4[0]);
            red_add_f32(dst + DM, a4[1]);
            red_add_f32(dst + 8, a4[2]);
            red_add_f32(dst + DM + 8, a4[3]);
        }
    }
    grid_arrive(&g_ctr[CT_B], tid);

    uint32_t xv[9], gav[9], cbv[9], sbv[9], gbv[9];
    {
        const __nv_bfloat16* md = g_mod + warp * (6 * DM);
#pragma unroll
        for (int i = 0; i < 9; i++) {
            const int col = 2 * (lane + 32 * i);
            xv[i] = *(const uint32_t*)(p.x + warp * DM + col);
            gav[i] = __ldcg((const uint32_t*)(md + 2 * DM + col));
            sbv[i] = __ldcg((const uint32_t*)(md + 3 * DM + col));
            cbv[i] = __ldcg((const uint32_t*)(md + 4 * DM + col));
            gbv[i] = __ldcg((const uint32_t*)(md + 5 * DM + col));
        }
    }
    grid_wait(&g_ctr[CT_B], NWORK, tid);
    float x1[18];
    {
        float sum = 0.f;
#pragma unroll
        for (int i = 0; i < 9; i++) {
            const float2 a = __ldcg((const float2*)(g_acc1 + warp * DM + 2 * (lane + 32 * i)));
            x1[2 * i] = bf_lo(xv[i]) + bf_lo(gav[i]) * a.x;
            x1[2 * i + 1] = bf_hi(xv[i]) + bf_hi(gav[i]) * a.y;
            sum += x1[2 * i] + x1[2 * i + 1];
        }
#pragma unroll
        for (int o = 16; o; o >>= 1) sum += __shfl_xor_sync(0xffffffffu, sum, o);
        const float mean = sum * (1.f / DM);
        float var = 0.f;
#pragma unroll
        for (int i = 0; i < 18; i++) { const float d = x1[i] - mean; var += d * d; }
#pragma unroll
        for (int o = 16; o; o >>= 1) var += __shfl_xor_sync(0xffffffffu, var, o);
        const float rstd = 1.f / sqrtf(var * (1.f / DM) + 1e-5f);
#pragma unroll
        for (int i = 0; i < 9; i++) {
            const float h0 = (x1[2 * i] - mean) * rstd * (1.f + bf_lo(cbv[i])) + bf_lo(sbv[i]);
            const float h1 = (x1[2 * i + 1] - mean) * rstd * (1.f + bf_hi(cbv[i])) + bf_hi(sbv[i]);
            *(uint32_t*)(s_in + warp * INP + 2 * (lane + 32 * i)) = pack_bf16(h0, h1);
        }
    }
    consumer_bar();
    {
        for (int i = 3; i < 9; i++) wwait(i);
        const int kq = warp & 3, grp = warp >> 2;
        const int mt0 = grp ? 3 : 0, nmt = grp ? 2 : 3;
        float a[3][4];
#pragma unroll
        for (int j = 0; j < 3; j++) a[j][0] = a[j][1] = a[j][2] = a[j][3] = 0.f;
        for (int ks = kq * 9; ks < kq * 9 + 9; ks++) {
            const int box = ks / 12, r0 = (ks % 12) * 16;
            const int row = r0 + (lane & 7) + ((lane >> 4) & 1) * 8;
            const uint32_t base = wslot(3 + box + (((lane >> 3) & 1) ? 3 : 0)) + row * 80;
            const uint32_t b0 = *(const uint32_t*)(s_in + g * INP + ks * 16 + 2 * c);
            const uint32_t b1 = *(const uint32_t*)(s_in + g * INP + ks * 16 + 2 * c + 8);
#pragma unroll
            for (int j = 0; j < 3; j++) {
                if (j < nmt) {
                    uint32_t a0, a1, a2, a3;
                    ldsm4t(base + (mt0 + j) * 16, a0, a1, a2, a3);
                    mma16816(a[j], a0, a1, a2, a3, b0, b1);
                }
            }
        }
        float* s_red = s_merge;
#pragma unroll
        for (int j = 0; j < 3; j++)
            if (j < nmt) {
#pragma unroll
                for (int i = 0; i < 4; i++) s_red[((kq * 5 + mt0 + j) * 4 + i) * 32 + lane] = a[j][i];
            }
        consumer_bar();
        __nv_bfloat16* s_act = (__nv_bfloat16*)(smem + SM_AUX + 9600);
        const int coff = (cta * 36) & 7;
        for (int e = tid; e < 8 * 48; e += 256) {
            const int b = e / 48, k = e % 48;
            float v = 0.f;
            if (k < 36) {
                const int col = k + coff, mt = col >> 3, gg = col & 7;
                const int l = gg * 4 + (b >> 1), i = b & 1;
                float gt = 0.f, up = 0.f;
#pragma unroll
                for (int q = 0; q < 4; q++) {
                    gt += s_red[((q * 5 + mt) * 4 + i) * 32 + l];
                    up += s_red[((q * 5 + mt) * 4 + 2 + i) * 32 + l];
                }
                const float inner = 0.7978845608028654f * (gt + 0.044715f * gt * gt * gt);
                v = 0.5f * gt * (1.f + tanhf(inner)) * up;
            }
            s_act[b * 56 + k] = __float2bfloat16(v);
        }
        consumer_bar();
        for (int i = 9; i < 12; i++) wwait(i);
        uint32_t bq[3][2], rowaddr[3];
#pragma unroll
        for (int ks = 0; ks < 3; ks++) {
            bq[ks][0] = *(const uint32_t*)(s_act + g * 56 + ks * 16 + 2 * c);
            bq[ks][1] = *(const uint32_t*)(s_act + g * 56 + ks * 16 + 2 * c + 8);
            int row = ks * 16 + (lane & 7) + ((lane >> 4) & 1) * 8;
            row = row < 36 ? row : 35;
            rowaddr[ks] = wslot(9 + row / 12) + (row % 12) * 1168 + ((lane >> 3) & 1) * 16;
        }
        for (int mt = warp; mt < 36; mt += 8) {
            float a4[4] = {0.f, 0.f, 0.f, 0.f};
#pragma unroll
            for (int ks = 0; ks < 3; ks++) {
                uint32_t a0, a1, a2, a3;
                ldsm4t(rowaddr[ks] + mt * 32, a0, a1, a2, a3);
                mma16816(a4, a0, a1, a2, a3, bq[ks][0], bq[ks][1]);
            }
            float* dst = g_acc2 + (2 * c) * DM + mt * 16 + g;
            red_add_f32(dst, a4[0]);
            red_add_f32(dst + DM, a4[1]);
            red_add_f32(dst + 8, a4[2]);
            red_add_f32(dst + DM + 8, a4[3]);
        }
    }
    __threadfence();
    consumer_bar();
    if (tid == 0) {
        unsigned old;
        asm volatile("atom.acq_rel.gpu.global.add.u32 %0, [%1], 1;" : "=r"(old) : "l"(&g_ctr[CT_C]) : "memory");
        *s_flag = (old == NWORK - 1) ? 1u : 0u;
    }
    consumer_bar();
    if (*s_flag) {
        __threadfence();
#pragma unroll
        for (int i = 0; i < 9; i++) {
            const int col = 2 * (lane + 32 * i);
            const float2 a = __ldcg((const float2*)(g_acc2 + warp * DM + col));
            *(uint32_t*)(p.out + warp * DM + col) =
                pack_bf16(x1[2 * i] + bf_lo(gbv[i]) * a.x, x1[2 * i + 1] + bf_hi(gbv[i]) * a.y);
        }
        if (tid < 6) g_ctr[tid * 32] = 0u;
    }
}

typedef CUresult (*EncodeFn)(CUtensorMap*, CUtensorMapDataType, cuuint32_t, void*, const cuuint64_t*, const cuuint64_t*,
                             const cuuint32_t*, const cuuint32_t*, CUtensorMapInterleave, CUtensorMapSwizzle,
                             CUtensorMapL2promotion, CUtensorMapFloatOOBfill);

void make_map(EncodeFn fn, CUtensorMap* m, const void* ptr, uint64_t inner, uint64_t rows, uint32_t box_inner,
              uint32_t box_rows, CUtensorMapSwizzle sw, CUtensorMapL2promotion promo) {
    cuuint64_t dims[2] = {inner, rows};
    cuuint64_t strides[1] = {inner * 2};
    cuuint32_t box[2] = {box_inner, box_rows};
    cuuint32_t es[2] = {1, 1};
    fn(m, CU_TENSOR_MAP_DATA_TYPE_BFLOAT16, 2, const_cast<void*>(ptr), dims, strides, box, es,
       CU_TENSOR_MAP_INTERLEAVE_NONE, sw, promo, CU_TENSOR_MAP_FLOAT_OOB_FILL_NONE);
}

}

extern "C" void kernel_launch(void* const* d_in, const int* in_sizes, int n_in, void* d_out, int out_size) {
    static EncodeFn fn = nullptr;
    static int nsm = 0;
    if (!fn) {
        cudaDriverEntryPointQueryResult qres;
        void* f = nullptr;
        cudaGetDriverEntryPoint("cuTensorMapEncodeTiled", &f, cudaEnableDefault, &qres);
        fn = (EncodeFn)f;
        int dev = 0;
        cudaGetDevice(&dev);
        cudaDeviceGetAttribute(&nsm, cudaDevAttrMultiProcessorCount, dev);
        cudaFuncSetAttribute(fused_kernel, cudaFuncAttributeMaxDynamicSharedMemorySize, SM_TOTAL);
    }
    CUtensorMap mK, mV, mMod, mQ, mG, mU;
    make_map(fn, &mK, d_in[1], 64, (uint64_t)NSLAB * SK * 2, 64, 64, CU_TENSOR_MAP_SWIZZLE_128B,
             CU_TENSOR_MAP_L2_PROMOTION_L2_128B);
    make_map(fn, &mV, d_in[2], 64, (uint64_t)NSLAB * SK * 2, 64, 64, CU_TENSOR_MAP_SWIZZLE_128B,
             CU_TENSOR_MAP_L2_PROMOTION_L2_128B);
    make_map(fn, &mQ, d_in[3], 4096, DM, 32, 192, CU_TENSOR_MAP_SWIZZLE_64B, CU_TENSOR_MAP_L2_PROMOTION_L2_128B);
    make_map(fn, &mMod, d_in[10], 6 * DM, DM, 32, 192, CU_TENSOR_MAP_SWIZZLE_64B, CU_TENSOR_MAP_L2_PROMOTION_L2_128B);
    make_map(fn, &mG, d_in[6], FF, DM, 40, 192, CU_TENSOR_MAP_SWIZZLE_NONE, CU_TENSOR_MAP_L2_PROMOTION_L2_128B);
    make_map(fn, &mU, d_in[7], FF, DM, 40, 192, CU_TENSOR_MAP_SWIZZLE_NONE, CU_TENSOR_MAP_L2_PROMOTION_L2_128B);
    Params p;
    p.x = (const __nv_bfloat16*)d_in[0];
    p.wo = (const __nv_bfloat16*)d_in[4];
    p.wdown = (const __nv_bfloat16*)d_in[8];
    p.c = (const __nv_bfloat16*)d_in[9];
    p.out = (__nv_bfloat16*)d_out;
    int grid = nsm < 132 ? nsm : 132;
    fused_kernel<<<grid, NTHREADS, SM_TOTAL>>>(mK, mV, mMod, mQ, mG, mU, p);
}
```

```cpp
#include <cuda_runtime.h>
#include <cuda_bf16.h>
#include <cuda.h>
#include <stdint.h>

namespace {

constexpr int NB = 8, DM = 576, SK = 8192, FF = 4608;
constexpr int NSLAB = 128;
constexpr int UPS = 256;
constexpr int NS = 12;
constexpr int SLOT = 16384;
constexpr int NCW = 8;
constexpr int NTHREADS = 384;
constexpr int NWORK = 128;
constexpr int NMODCTA = 108;
constexpr int NHCTA = 36;
constexpr int NRED = 72;

constexpr int PPS = 13;
constexpr int RPS = 14;
constexpr int JLATE = 9;
constexpr int NA = NSLAB * 7;
constexpr int NL = NA + 4 * NSLAB;
constexpr int NITEMS = NSLAB * PPS;

#define CFG_IFL 4
#define CFG_IFL0 3
#define CFG_IFL0N 12
#define CFG_IFLT 3
#define CFG_IFLTAT 1152
#define CFG_IFLW 2
#define CFG_IFLD 2
#define CFG_PP 0
#define CFG_PD 1000
#define CFG_PD1 0
#define CFG_WHAT 9
#define CFG_DRYAT 1152
#define CFG_CLRAT 512
#define CFG_RQ 1
#define CFG_RQL 4
#define CFG_TB 1
#define CFG_T1E 0
#define CFG_WH 3
#define CFG_EVF 1
#define CFG_DRY 15
#define CFG_LATE0 1
#define CFG_WARM 1
#define CFG_TD 0
#define CFG_PW 1
#define CFG_TQ 1
#define CFG_WQD 1700
#define CFG_KVD 2500
#define CFG_L1 2
#define CFG_HOLD 0

constexpr int NMB = 4;
constexpr int MERGE_W = 264;
constexpr int SM_MERGE = NS * SLOT;
constexpr int SM_BAR = SM_MERGE + NMB * NCW * MERGE_W * 4;
constexpr int SM_TOTAL = SM_BAR + 2048;
constexpr int INP = 584;
constexpr int SC_C = 0;
constexpr int SC_H = 9344;
constexpr int SC_RED = 18688;
constexpr int SC_RR = 28928;
constexpr int SB_FULL = 0, SB_EMPTY = 96;
constexpr int SB_T1 = 192, SB_CLRB = 200, SB_P0 = 208;
constexpr int SB_META = 256;
constexpr int SB_GEN = 512, SB_CNT = 528, SB_REQ = 544, SB_FLAG = 548, SB_FIN = 552, SB_FLAG2 = 556, SB_ITEM = 560, SB_STAT = 576;
constexpr int SB_B = 1024;
constexpr int W_T1 = 6 * SLOT, W_T2 = 9 * SLOT;

constexpr float SCALE_LOG2 = 0.08838834764831845f * 1.4426950408889634f;
constexpr float NEG = -1e30f;

__device__ __align__(128) ulonglong2 g_part[(size_t)NSLAB * RPS * 2 * 4 * 18];
__device__ __align__(128) ulonglong2 g_h[NB * 144];
__device__ __align__(128) ulonglong2 g_q[NB * 32 * 32];
__device__ __align__(128) ulonglong2 g_mod[NB * 4 * 144];
__device__ __align__(128) ulonglong2 g_x1[NB * 144];
__device__ __align__(128) float4 g_r[2 * NRED * NWORK * 16];
__device__ __align__(128) unsigned g_epoch[32];
__device__ __align__(128) unsigned g_clr[32];
__device__ __align__(128) unsigned g_item[64];

#define HSTAMP(i)
#define STAMP(i)
#define STAMPW(i)
#define PSTAMP(i)
#define USTAMP(u, k)
#define WSTAMP(k)

#define PRED(n) "{\n.reg .pred q;\nsetp.ne.u32 q, %" #n ", 0;\n@q "
__device__ __forceinline__ uint32_t smem_u32(const void* p) { return (uint32_t)__cvta_generic_to_shared(p); }
__device__ __forceinline__ void mbar_init(uint32_t bar, uint32_t cnt) {
    asm volatile("mbarrier.init.shared::cta.b64 [%0], %1;" ::"r"(bar), "r"(cnt));
}
__device__ __forceinline__ void mbar_expect_tx(uint32_t bar, uint32_t bytes) {
    asm volatile("mbarrier.arrive.expect_tx.shared::cta.b64 _, [%0], %1;" ::"r"(bar), "r"(bytes) : "memory");
}
__device__ __forceinline__ void mbar_arrive(uint32_t bar, uint32_t q) {
    asm volatile(PRED(1) "mbarrier.arrive.shared::cta.b64 _, [%0];\n}" ::"r"(bar), "r"(q) : "memory");
}
__device__ __forceinline__ bool mbar_test(uint32_t bar, uint32_t parity) {
    uint32_t ok;
    asm volatile("{\n.reg .pred p;\nmbarrier.test_wait.parity.shared::cta.b64 p, [%1], %2;\nselp.u32 %0, 1, 0, p;\n}"
                 : "=r"(ok) : "r"(bar), "r"(parity) : "memory");
    return ok != 0;
}
__device__ __forceinline__ uint32_t mbar_test_q(uint32_t bar, uint32_t parity, uint32_t q) {
    uint32_t ok;
    asm volatile("{\n.reg .pred p, q;\nsetp.ne.u32 q, %3, 0;\nsetp.ne.u32 p, %3, %3;\n"
                 "@q mbarrier.test_wait.parity.shared::cta.b64 p, [%1], %2;\nselp.u32 %0, 1, 0, p;\n}"
                 : "=r"(ok) : "r"(bar), "r"(parity), "r"(q) : "memory");
    return ok;
}
__device__ __forceinline__ void mbar_wait(uint32_t bar, uint32_t parity, uint32_t q) {
    asm volatile("{\n.reg .pred p;\n.reg .u32 n;\nsetp.eq.u32 p, %2, 0;\n@p bra.uni WDONE;\nmov.u32 n, 0;\n"
                 "WLOOP:\nmbarrier.try_wait.parity.shared::cta.b64 p, [%0], %1;\n@p bra WDONE;\n"
                 "add.u32 n, n, 1;\nsetp.lt.u32 p, n, 0x400000;\n@p bra WLOOP;\ntrap;\nWDONE:\n}"
                 ::"r"(bar), "r"(parity), "r"(q) : "memory");
}
#define SPIN(n, lim) do { if (++(n) > (lim)) __trap(); } while (0)
constexpr uint32_t LIM_G = 1u << 22;
constexpr uint32_t LIM_S = 1u << 26;
__device__ __forceinline__ void tma2d(uint32_t dst, const CUtensorMap* map, int c0, int c1, uint32_t bar, uint64_t pol) {
    asm volatile("cp.async.bulk.tensor.2d.shared::cluster.global.mbarrier::complete_tx::bytes.L2::cache_hint [%0], [%1, {%3, %4}], [%2], %5;"
                 ::"r"(dst), "l"((uint64_t)map), "r"(bar), "r"(c0), "r"(c1), "l"(pol) : "memory");
}
__device__ __forceinline__ void tma3d(uint32_t dst, const CUtensorMap* map, int c0, int c1, int c2, uint32_t bar) {
    asm volatile("cp.async.bulk.tensor.3d.shared::cluster.global.mbarrier::complete_tx::bytes [%0], [%1, {%3, %4, %5}], [%2];"
                 ::"r"(dst), "l"((uint64_t)map), "r"(bar), "r"(c0), "r"(c1), "r"(c2) : "memory");
}
__device__ __forceinline__ void l2_prefetch(const void* p, uint32_t bytes) {
    asm volatile("cp.async.bulk.prefetch.L2.global [%0], %1;" ::"l"(p), "r"(bytes) : "memory");
}
__device__ __forceinline__ void prefetch_map(const CUtensorMap* map) {
    asm volatile("prefetch.tensormap [%0];" ::"l"((uint64_t)map) : "memory");
}
__device__ __forceinline__ void cp16(uint32_t dst, const void* src, uint32_t q) {
    asm volatile(PRED(2) "cp.async.cg.shared.global [%0], [%1], 16;\n}" ::"r"(dst), "l"(src), "r"(q) : "memory");
}
__device__ __forceinline__ void ldsm4(uint32_t addr, uint32_t& r0, uint32_t& r1, uint32_t& r2, uint32_t& r3) {
    asm volatile("ldmatrix.sync.aligned.m8n8.x4.shared.b16 {%0,%1,%2,%3}, [%4];"
                 : "=r"(r0), "=r"(r1), "=r"(r2), "=r"(r3) : "r"(addr) : "memory");
}
__device__ __forceinline__ void ldsm4t(uint32_t addr, uint32_t& r0, uint32_t& r1, uint32_t& r2, uint32_t& r3) {
    asm volatile("ldmatrix.sync.aligned.m8n8.x4.trans.shared.b16 {%0,%1,%2,%3}, [%4];"
                 : "=r"(r0), "=r"(r1), "=r"(r2), "=r"(r3) : "r"(addr) : "memory");
}
__device__ __forceinline__ void mma16816(float* c, uint32_t a0, uint32_t a1, uint32_t a2, uint32_t a3, uint32_t b0,
                                         uint32_t b1) {
    asm volatile("mma.sync.aligned.m16n8k16.row.col.f32.bf16.bf16.f32 {%0,%1,%2,%3}, {%4,%5,%6,%7}, {%8,%9}, {%0,%1,%2,%3};"
                 : "+f"(c[0]), "+f"(c[1]), "+f"(c[2]), "+f"(c[3])
                 : "r"(a0), "r"(a1), "r"(a2), "r"(a3), "r"(b0), "r"(b1));
}
__device__ __forceinline__ uint32_t pack_bf16(float lo, float hi) {
    uint32_t r;
    asm("cvt.rn.bf16x2.f32 %0, %1, %2;" : "=r"(r) : "f"(hi), "f"(lo));
    return r;
}
__device__ __forceinline__ float bf_lo(uint32_t v) { return __uint_as_float(v << 16); }
__device__ __forceinline__ float bf_hi(uint32_t v) { return __uint_as_float(v & 0xffff0000u); }
__device__ __forceinline__ float ex2(float x) {
    float r;
    asm("ex2.approx.ftz.f32 %0, %1;" : "=f"(r) : "f"(x));
    return r;
}
__device__ __forceinline__ void cbar(uint32_t q) { asm volatile(PRED(0) "bar.sync 1, 256;\n}" ::"r"(q) : "memory"); }
__device__ __forceinline__ void sts16(uint32_t a, uint16_t v, uint32_t q) {
    asm volatile(PRED(2) "st.shared.b16 [%0], %1;\n}" ::"r"(a), "h"(v), "r"(q) : "memory");
}
__device__ __forceinline__ void sts32(uint32_t a, uint32_t v, uint32_t q) {
    asm volatile(PRED(2) "st.shared.b32 [%0], %1;\n}" ::"r"(a), "r"(v), "r"(q) : "memory");
}
__device__ __forceinline__ void stsf(uint32_t a, float v, uint32_t q) { sts32(a, __float_as_uint(v), q); }
__device__ __forceinline__ void sts64(uint32_t a, uint32_t x, uint32_t y, uint32_t q) {
    asm volatile(PRED(3) "st.shared.v2.b32 [%0], {%1, %2};\n}" ::"r"(a), "r"(x), "r"(y), "r"(q) : "memory");
}
__device__ __forceinline__ void sts128(uint32_t a, uint32_t x, uint32_t y, uint32_t z, uint32_t w, uint32_t q) {
    asm volatile(PRED(5) "st.shared.v4.b32 [%0], {%1, %2, %3, %4};\n}" ::"r"(a), "r"(x), "r"(y), "r"(z), "r"(w), "r"(q) : "memory");
}
__device__ __forceinline__ uint32_t lds32(uint32_t a) {
    uint32_t v;
    asm volatile("ld.shared.b32 %0, [%1];" : "=r"(v) : "r"(a) : "memory");
    return v;
}
__device__ __forceinline__ float ldsf(uint32_t a) { return __uint_as_float(lds32(a)); }
__device__ __forceinline__ float2 ldsf2(uint32_t a) {
    float2 v;
    asm volatile("ld.shared.v2.f32 {%0, %1}, [%2];" : "=f"(v.x), "=f"(v.y) : "r"(a) : "memory");
    return v;
}
__device__ __forceinline__ uint64_t lds64v(uint32_t a) {
    uint64_t v;
    asm volatile("ld.volatile.shared.b64 %0, [%1];" : "=l"(v) : "r"(a) : "memory");
    return v;
}
__device__ __forceinline__ uint32_t lds32v(uint32_t a) {
    uint32_t v;
    asm volatile("ld.volatile.shared.b32 %0, [%1];" : "=r"(v) : "r"(a) : "memory");
    return v;
}
__device__ __forceinline__ void sts32v(uint32_t a, uint32_t v, uint32_t q) {
    asm volatile(PRED(2) "st.volatile.shared.b32 [%0], %1;\n}" ::"r"(a), "r"(v), "r"(q) : "memory");
}
__device__ __forceinline__ void sts64v(uint32_t a, uint64_t v) {
    asm volatile("st.volatile.shared.b64 [%0], %1;" ::"r"(a), "l"(v) : "memory");
}

__device__ __forceinline__ uint64_t tagw(uint32_t w, uint32_t tag) { return (uint64_t)w | ((uint64_t)tag << 32); }
__device__ __forceinline__ void st_ll(void* p, uint64_t a, uint32_t q) {
    asm volatile(PRED(2) "st.relaxed.gpu.global.b64 [%0], %1;\n}" ::"l"(p), "l"(a), "r"(q) : "memory");
}
__device__ __forceinline__ void st_ll2(void* p, uint64_t a, uint64_t b, uint32_t q) {
    asm volatile(PRED(3) "st.relaxed.gpu.global.v2.b64 [%0], {%1, %2};\n}" ::"l"(p), "l"(a), "l"(b), "r"(q) : "memory");
}
__device__ __forceinline__ uint64_t ld_ll(const void* p, uint32_t q) {
    uint64_t a;
    asm volatile("mov.b64 %0, 0;\n" PRED(2) "ld.relaxed.gpu.global.b64 %0, [%1];\n}" : "=l"(a) : "l"(p), "r"(q) : "memory");
    return a;
}
__device__ __forceinline__ ulonglong2 ld_ll2(const void* p, uint32_t q) {
    ulonglong2 v;
    asm volatile("mov.b64 %0, 0;\nmov.b64 %1, 0;\n" PRED(3) "ld.relaxed.gpu.global.v2.b64 {%0, %1}, [%2];\n}"
                 : "=l"(v.x), "=l"(v.y) : "l"(p), "r"(q) : "memory");
    return v;
}
__device__ __forceinline__ void ld_ll2k(ulonglong2& v, const void* p, uint32_t q) {
    asm volatile(PRED(3) "ld.relaxed.gpu.global.v2.b64 {%0, %1}, [%2];\n}" : "+l"(v.x), "+l"(v.y) : "l"(p), "r"(q) : "memory");
}
__device__ __forceinline__ bool ll_ok(const ulonglong2& v, uint32_t tag) {
    return (uint32_t)(v.x >> 32) == tag && (uint32_t)(v.y >> 32) == tag;
}
__device__ __forceinline__ void st_r4(void* p, uint32_t a, uint32_t b, uint32_t c, uint32_t d, uint32_t q) {
    asm volatile(PRED(5) "st.relaxed.gpu.global.v4.b32 [%0], {%1, %2, %3, %4};\n}" ::"l"(p), "r"(a), "r"(b), "r"(c), "r"(d), "r"(q) : "memory");
}
__device__ __forceinline__ void ld_r4k(uint4& v, const void* p, uint32_t q) {
    asm volatile(PRED(5) "ld.relaxed.gpu.global.v4.b32 {%0, %1, %2, %3}, [%4];\n}"
                 : "+r"(v.x), "+r"(v.y), "+r"(v.z), "+r"(v.w) : "l"(p), "r"(q) : "memory");
}
__device__ __forceinline__ uint32_t nz(float v) {
    const uint32_t u = __float_as_uint(v);
    return u ? u : 0x80000000u;
}
__device__ __forceinline__ uint32_t ld_u32(const unsigned* p) {
    uint32_t v;
    asm volatile("ld.relaxed.gpu.global.u32 %0, [%1];" : "=r"(v) : "l"(p) : "memory");
    return v;
}
__device__ __forceinline__ uint32_t ld_acq(const unsigned* p, uint32_t q) {
    uint32_t v;
    asm volatile("mov.b32 %0, 0;\n" PRED(2) "ld.acquire.gpu.global.u32 %0, [%1];\n}" : "=r"(v) : "l"(p), "r"(q) : "memory");
    return v;
}
__device__ __forceinline__ uint4 ldg16(const void* p, uint32_t q) {
    uint4 v;
    asm volatile("mov.b32 %0, 0;\nmov.b32 %1, 0;\nmov.b32 %2, 0;\nmov.b32 %3, 0;\n" PRED(5) "ld.global.nc.v4.b32 {%0, %1, %2, %3}, [%4];\n}"
                 : "=r"(v.x), "=r"(v.y), "=r"(v.z), "=r"(v.w) : "l"(p), "r"(q));
    return v;
}
__device__ __forceinline__ uint2 ldg8(const void* p, uint32_t q) {
    uint2 v;
    asm volatile("mov.b32 %0, 0;\nmov.b32 %1, 0;\n" PRED(3) "ld.global.nc.v2.b32 {%0, %1}, [%2];\n}" : "=r"(v.x), "=r"(v.y) : "l"(p), "r"(q));
    return v;
}
__device__ __forceinline__ uint32_t ldg4(const void* p, uint32_t q) {
    uint32_t v;
    asm volatile("mov.b32 %0, 0;\n" PRED(2) "ld.global.nc.b32 %0, [%1];\n}" : "=r"(v) : "l"(p), "r"(q));
    return v;
}

struct Params {
    const __nv_bfloat16* x;
    const __nv_bfloat16* c;
    const __nv_bfloat16* wq;
    const __nv_bfloat16* wmod;
    const __nv_bfloat16* wdown;
    __nv_bfloat16* out;
};

constexpr uint32_t MF_FIRST = 1u << 23, MF_LAST = 1u << 24, MF_END = 1u << 25;
constexpr uint32_t REQ_STOP = 0xFFFFFFFFu;

__device__ __forceinline__ uint32_t piece_slot(uint32_t fin, int k) {
    const uint32_t s = (fin & 15) + k;
    return s >= NS ? s - NS : s;
}
template <int N>
__device__ __forceinline__ void wait_pieces(uint32_t full0, uint32_t fin, int k0, uint32_t live) {
    uint32_t ok = 1;
#pragma unroll
    for (int k = 0; k < N; k++) {
        const uint32_t s = piece_slot(fin, k0 + k);
        ok &= mbar_test_q(full0 + 8 * s, (fin >> (4 + s)) & 1, live);
    }
    if (!ok) {
#pragma unroll 1
        for (int k = 0; k < N; k++) {
            const uint32_t s = piece_slot(fin, k0 + k);
            mbar_wait(full0 + 8 * s, (fin >> (4 + s)) & 1, live);
        }
    }
}

__device__ __forceinline__ void poll_row(const ulonglong2* row, uint32_t tag, int lane, uint32_t live, uint32_t (&w)[10]) {
    uint32_t pend = live ? (lane < 16 ? 31u : 15u) : 0u;
    ulonglong2 v[5];
#pragma unroll
    for (int i = 0; i < 5; i++) v[i].x = v[i].y = 0ull;
    uint32_t n = 0;
    do {
#pragma unroll
        for (int i = 0; i < 5; i++) ld_ll2k(v[i], row + lane + 32 * i, pend >> i & 1);
#pragma unroll
        for (int i = 0; i < 5; i++)
            if (ll_ok(v[i], tag)) pend &= ~(1u << i);
        SPIN(n, LIM_G);
    } while (__any_sync(0xffffffffu, pend != 0));
#pragma unroll
    for (int i = 0; i < 5; i++) { w[2 * i] = (uint32_t)v[i].x; w[2 * i + 1] = (uint32_t)v[i].y; }
}

__global__ void __launch_bounds__(NTHREADS, 1)
fused_kernel(const __grid_constant__ CUtensorMap mapK, const __grid_constant__ CUtensorMap mapV,
             const __grid_constant__ CUtensorMap mapWo, const __grid_constant__ CUtensorMap mapG,
             const __grid_constant__ CUtensorMap mapU, const __grid_constant__ CUtensorMap mapD,
             const __grid_constant__ CUtensorMap mapQ, const __grid_constant__ CUtensorMap mapM,
             const __grid_constant__ CUtensorMap mapMh, const Params p) {
    extern __shared__ __align__(1024) unsigned char smem[];
    const uint32_t ring = smem_u32(smem);
    const uint32_t smrg = ring + SM_MERGE, sbar = ring + SM_BAR;
    const uint32_t full0 = sbar + SB_FULL, empty0 = sbar + SB_EMPTY;
    const int wrp = threadIdx.x >> 5, lane = threadIdx.x & 31;
    const int cta = blockIdx.x, ncta = gridDim.x;
    const uint32_t ep = ld_u32(g_epoch);

    if (wrp == NCW) {
        if (lane == 0) {
            mbar_init(sbar + SB_P0, 1);
            mbar_init(sbar + SB_P0 + 8, 1);
            asm volatile("fence.mbarrier_init.release.cluster;" ::: "memory");
            if (cta < NHCTA) {
                mbar_expect_tx(sbar + SB_P0, 36864);
                tma3d(ring + W_T1, &mapMh, cta * 16, 0, 0, sbar + SB_P0);
                tma3d(ring + W_T1 + 18432, &mapMh, DM + cta * 16, 0, 0, sbar + SB_P0);
            }
            if (cta >= NHCTA && cta < NMODCTA) {
                mbar_expect_tx(sbar + SB_P0, 36864);
                tma3d(ring + W_T1, &mapM, 2 * DM + (cta - NHCTA) * 32, 0, 0, sbar + SB_P0);
            }
            if (cta < NWORK) {
                mbar_expect_tx(sbar + SB_P0 + 8, 36864);
                tma3d(ring + W_T2, &mapQ, cta * 32, 0, 0, sbar + SB_P0 + 8);
            }
            prefetch_map(&mapK);
            prefetch_map(&mapV);
            for (int s = 0; s < 2 * NS; s++) mbar_init(full0 + 8 * s, 1);
            mbar_init(sbar + SB_T1, NCW);
            mbar_init(sbar + SB_CLRB, 1);
            for (int i = 0; i < 16; i++) sts32(sbar + SB_GEN + 4 * i, 0u, 1);
            asm volatile("fence.mbarrier_init.release.cluster;" ::: "memory");
        }
        sts64v(sbar + SB_META + 8 * lane, 0xFFFFull);
        __syncwarp();
        asm volatile("bar.arrive 0, 288;" ::: "memory");
        asm volatile("bar.arrive 2, 64;" ::: "memory");
        asm volatile("bar.arrive 3, 96;" ::: "memory");
        if (lane == 0) {
            if (cta < NMODCTA) mbar_wait(sbar + SB_P0, 0, 1);
            PSTAMP(51);
            uint64_t pol = 0;
            asm volatile("createpolicy.fractional.L2::evict_first.b64 %0, 1.0;" : "=l"(pol));
            uint32_t u = 0;
            int slot = 0;
            uint32_t phF = 0, phE = 0x3Fu;
            uint32_t hist = 0;
            uint32_t cc = 0;
            uint32_t nreq = 0, ngot = 0, spins = 0;
            bool fin = false;
            int idx = cta, n = 0, i = 0, unit0 = 0;
            uint32_t lo0 = 0, hi0 = 0;
            while (true) {
                if (i == n) {
                    if (fin) break;
                    if (u) {
                        uint32_t v;
                        while (((v = lds32v(sbar + SB_ITEM + 4 * (ngot & 3))) >> 16) != ngot + 1) SPIN(spins, LIM_S);
                        ngot++;
                        idx = (int)(v & 0xFFFFu);
                    } else if (cta == 0) g_item[((ep + 1) & 1) * 32] = 0u;
                    i = 0;
                    if (idx >= NITEMS) {
                        fin = true;
                        sts32v(sbar + SB_FLAG, 1u, 1);
                        sts32v(sbar + SB_FLAG2, 1u, 1);
                        PSTAMP(40);
                        sts32v(sbar + SB_FIN, (uint32_t)slot | (phF << 4), 1);
                        for (int k = 0; k < NCW; k++)
                            sts64v(sbar + SB_META + 8 * ((u + k) & 31), (uint64_t)(MF_END | ((u + k) & 0xFFFFu)));
                        sts32v(sbar + SB_REQ, REQ_STOP, 1);
                        if (cta >= NWORK) break;
                        n = NS;
                        prefetch_map(&mapWo);
                        prefetch_map(&mapG);
                        prefetch_map(&mapU);
                        prefetch_map(&mapD);
                    } else {
                        int slab, jj;
                        if (idx < NA) { slab = idx / 7; jj = idx - slab * 7; }
                        else if (idx < NL) { slab = (idx - NA) & 127; jj = 7 + ((idx - NA) >> 7); }
                        else { slab = (idx - NL) >> 1; jj = 11 + ((idx - NL) & 1); }
                        n = jj < 7 ? 32 : (jj >= 11 ? 1 : 16 >> (jj - 7));
                        unit0 = slab * UPS + (jj < 7 ? 32 * jj : (jj == 12 ? 255 : 256 - 2 * n));
                        if (n <= 2) {
                            nreq = max(nreq, ngot + 3 - n);
                            sts32v(sbar + SB_REQ, nreq, 1);
                        }
                        if (idx >= CFG_DRYAT) sts32v(sbar + SB_FLAG, 1u, 1);
                        if (idx >= CFG_CLRAT) sts32v(sbar + SB_FLAG2, 1u, 1);
                        lo0 = (uint32_t)slab << 16;
                        hi0 = (uint32_t)(slab * RPS + jj) | (jj >= JLATE ? 1u << 11 : 0u) | ((uint32_t)(n < NCW ? n : NCW) << 16) |
                              ((cc & (NMB - 1)) << 20) | (((cc / NMB) & 255u) << 22);
                        if (n > 1) cc++;
                    }
                }
                if (!fin && (n > 4 ? i == n - CFG_RQL : (n == 4 ? i == 1 : (n == 2 && i == 1)))) {
                    nreq = max(nreq, ngot + (n == 2 ? 2 : 1));
                    sts32v(sbar + SB_REQ, nreq, 1);
                }
                if ((CFG_WH & 4) && fin && i == CFG_WHAT) mbar_wait(sbar + SB_T1, 0, 1);
                uint32_t ifl = fin ? (i >= 9 ? CFG_IFLD : CFG_IFLW) : (u < CFG_IFL0N ? CFG_IFL0 : (idx >= CFG_IFLTAT ? CFG_IFLT : CFG_IFL));
                if ((CFG_WH & 1) && fin && i == 0) ifl = 1;
                if ((CFG_WH & 2) && fin && i == 3) {
                    for (int k = 1; k <= NCW; k++) {
                        const int s = (slot + 2 * NS - 3 - k) % NS;
                        mbar_wait(empty0 + 8 * s, (phE >> s) & 1, 1);
                    }
                }
                if (ifl <= 6 && u >= ifl) {
                    const uint32_t e = hist >> (5 * (ifl - 1));
                    mbar_wait(full0 + 8 * (e & 15), (e >> 4) & 1, 1);
                }
                mbar_wait(empty0 + 8 * slot, (phE >> slot) & 1, 1);
                phE ^= 1u << slot;
                const uint32_t par = (phF >> slot) & 1;
                phF ^= 1u << slot;
                const uint32_t fb = full0 + 8 * slot, dst = ring + slot * SLOT;
                if (!fin) {
                    mbar_expect_tx(fb, SLOT);
                    tma2d(dst, &mapK, 0, (unit0 + i) * 64, fb, pol);
                    tma2d(dst + 8192, &mapV, 0, (unit0 + i) * 64, fb, pol);
                    const uint32_t lo = lo0 | (u & 0xFFFFu) | (i < NCW ? MF_FIRST : 0u) | (i + NCW >= n ? MF_LAST : 0u) |
                                        ((uint32_t)slot << 27) | (par << 31);
                    const uint32_t hi = hi0 | ((uint32_t)(i & 7) << 13);
                    sts64v(sbar + SB_META + 8 * (u & 31), (uint64_t)lo | ((uint64_t)hi << 32));
                } else {
                    const bool gu = i >= 3 && i < 9;
                    mbar_expect_tx(fb, i < 3 ? 12288 : 15360);
                    const CUtensorMap* mp = gu ? (i < 6 ? &mapG : &mapU) : (i < 3 ? &mapWo : &mapD);
                    const int k3 = i % 3;
                    tma3d(dst, mp, gu ? (cta * 36) & ~7 : 0, gu ? 0 : (i < 3 ? cta * 32 : cta * 36), gu ? k3 : 3 * k3, fb);
                    if (i == 0) PSTAMP(41);
                }
                hist = (hist << 5) | (uint32_t)slot | (par << 4);
                u++;
                i++;
                if (++slot == NS) slot = 0;
            }
            PSTAMP(42);
        }
        return;
    }

    uint32_t live = wrp < NCW ? 1u : 0u;
    asm volatile("" : "+r"(live));
    const int role = wrp - NCW;
    const int warp = live ? wrp : 0, tid = warp * 32 + lane;
    const int g = lane >> 2, c = lane & 3;
    const uint32_t tag = ep + 1;
    const uint32_t s_c = smrg + SC_C, s_h = smrg + SC_H, s_red = smrg + SC_RED, s_stat = sbar + SB_STAT;
    const int lrow = (lane & 7) + ((lane >> 4) & 1) * 8, cb1 = (lane >> 3) & 1;

    uint32_t xs0 = 0, xs1 = 0;
    if (live || (role == 3 && (CFG_DRY & 8))) {
        uint2 xv[5];
        {
            const uint32_t on = live && cta < NHCTA;
#pragma unroll
            for (int i = 0; i < 5; i++) xv[i] = ldg8(p.x + warp * DM + (lane + 32 * i) * 4, on && lane + 32 * i < 144);
            const __nv_bfloat16* xp = p.x + (2 * c + (warp & 1)) * DM + cta * 16 + (g & ~1);
            xs0 = ldg4(xp, on); xs1 = ldg4(xp + 8, on);
        }
#pragma unroll
        for (int i = 0; i < 3; i++) {
            const int idx = tid + 256 * i;
            cp16(s_c + ((idx / 72) * INP + (idx % 72) * 8) * 2, p.c + idx * 8, live && cta < NMODCTA && idx < 576);
        }
        asm volatile("cp.async.commit_group;" ::: "memory");
        STAMP(0);
        asm volatile("cp.async.wait_group 0;" ::: "memory");
        if (cta < NMODCTA) {
#pragma unroll 1
            for (int i = 0; i < 3; i++) {
                const int idx = tid + 256 * i;
                if (idx >= 576) break;
                const uint32_t a = s_c + ((idx / 72) * INP + (idx % 72) * 8) * 2;
                uint32_t w[4];
                asm volatile("ld.shared.v4.b32 {%0, %1, %2, %3}, [%4];" : "=r"(w[0]), "=r"(w[1]), "=r"(w[2]), "=r"(w[3]) : "r"(a) : "memory");
#pragma unroll
                for (int j = 0; j < 4; j++) {
                    const float a = bf_lo(w[j]), b = bf_hi(w[j]);
                    w[j] = pack_bf16(__fdividef(a, 1.f + __expf(-a)), __fdividef(b, 1.f + __expf(-b)));
                }
                sts128(a, w[0], w[1], w[2], w[3], live);
            }
        }
        if (cta < NHCTA) {
            float sum = 0.f;
#pragma unroll
            for (int i = 0; i < 5; i++) sum += (bf_lo(xv[i].x) + bf_hi(xv[i].x)) + (bf_lo(xv[i].y) + bf_hi(xv[i].y));
#pragma unroll
            for (int o = 16; o; o >>= 1) sum += __shfl_xor_sync(0xffffffffu, sum, o);
            const float mean = sum * (1.f / DM);
            float var = 0.f;
#pragma unroll
            for (int i = 0; i < 5; i++)
                if (lane + 32 * i < 144) {
                    const float d0 = bf_lo(xv[i].x) - mean, d1 = bf_hi(xv[i].x) - mean;
                    const float d2 = bf_lo(xv[i].y) - mean, d3 = bf_hi(xv[i].y) - mean;
                    var += (d0 * d0 + d1 * d1) + (d2 * d2 + d3 * d3);
                }
#pragma unroll
            for (int o = 16; o; o >>= 1) var += __shfl_xor_sync(0xffffffffu, var, o);
            const float rstd = rsqrtf(var * (1.f / DM) + 1e-5f);
            stsf(s_stat + warp * 8, mean, live && lane == 0);
            stsf(s_stat + warp * 8 + 4, rstd, live && lane == 0);
        }
        STAMP(32);
        if (live) asm volatile("bar.sync 0, 288;" ::: "memory");
    }
    if (live || (role == 1 && (CFG_DRY & 1))) {
        const uint32_t so0 = lrow * 64 + ((cb1 ^ ((lrow >> 1) & 3)) << 4);
        const uint32_t so1 = lrow * 64 + (((2 + cb1) ^ ((lrow >> 1) & 3)) << 4);
        const uint32_t sh0 = lrow * 32 + ((cb1 ^ ((lrow >> 2) & 1)) << 4);
        HSTAMP(48);
#pragma unroll 1
        for (int jj = 0; jj < 2 + CFG_WARM; jj++) {
            const int j = jj ? 1 : 0;
            const uint32_t real = live && !(CFG_WARM && jj == 1);
            const int kind = cta < NHCTA ? j : 2 - j;
            if (kind == 1 ? cta >= NWORK : cta >= NMODCTA) {
                for (int i = 6; i < 9; i++) mbar_arrive(empty0 + 8 * (i + 3 * j), real && tid == 0);
                continue;
            }
            if (kind == 1) {
                uint32_t w[10];
                poll_row(g_h + warp * 144, tag, lane, real, w);
                STAMP(2);
#pragma unroll
                for (int i = 0; i < 5; i++) {
                    const int un = lane + 32 * i;
                    const uint32_t d = s_h + (warp * INP + (un >> 2) * 16 + (un & 3) * 2) * 2;
                    sts32(d, w[2 * i], live && un < 144);
                    sts32(d + 16, w[2 * i + 1], live && un < 144);
                }
            }
            mbar_wait(sbar + SB_P0 + 8 * j, 0, real);
            cbar(live);
            STAMP(35 + j);
            {
                const uint32_t tile = ring + (j ? W_T2 : W_T1);
                const uint32_t in = (kind == 1 ? s_h : s_c) + (g * INP + 2 * c) * 2;
                const uint32_t st = kind ? 1024u : 512u;
                const uint32_t t0 = tile + warp * st + (kind ? so0 : sh0), t1 = tile + warp * st + (kind ? so1 : sh0 + 18432u);
                float acc[2][4] = {{0.f, 0.f, 0.f, 0.f}, {0.f, 0.f, 0.f, 0.f}};
#pragma unroll
                for (int i = 0; i < 5; i++) {
                    const int s = warp + 8 * i;
                    if (s < 36) {
                        const uint32_t b0 = lds32(in + s * 32), b1 = lds32(in + s * 32 + 16);
                        uint32_t a0, a1, a2, a3;
                        ldsm4t(t0 + i * 8 * st, a0, a1, a2, a3);
                        mma16816(acc[0], a0, a1, a2, a3, b0, b1);
                        ldsm4t(t1 + i * 8 * st, a0, a1, a2, a3);
                        mma16816(acc[1], a0, a1, a2, a3, b0, b1);
                    }
                }
#pragma unroll
                for (int mt = 0; mt < 2; mt++)
#pragma unroll
                    for (int i = 0; i < 4; i++) stsf(s_red + (warp * 256 + (mt * 4 + i) * 32 + lane) * 4, acc[mt][i], live);
            }
            cbar(live);
            if (tid >= 64)
                for (int i = 6; i < 9; i++) mbar_arrive(empty0 + 8 * (i + 3 * j), real && tid == 64);
            if (tid < 64) {
                float a0 = 0.f, a1 = 0.f, c0 = 0.f, c1 = 0.f;
                const uint32_t r = s_red + tid * 4;
#pragma unroll
                for (int w = 0; w < 8; w++) {
                    a0 += ldsf(r + w * 1024); a1 += ldsf(r + w * 1024 + 256);
                    c0 += ldsf(r + w * 1024 + 512); c1 += ldsf(r + w * 1024 + 768);
                }
                const uint32_t sa = pack_bf16(a0, a1), ca = pack_bf16(c0, c1);
                const uint32_t san = __shfl_down_sync(0xffffffffu, sa, 4), can = __shfl_down_sync(0xffffffffu, ca, 4);
                const int b = 2 * c + warp;
                const uint32_t qs = real && !(g & 1);
                if (kind == 0) {
                    const float2 st = ldsf2(s_stat + b * 8);
                    const float h00 = (bf_lo(xs0) - st.x) * st.y * (1.f + bf_lo(ca)) + bf_lo(sa);
                    const float h01 = (bf_hi(xs0) - st.x) * st.y * (1.f + bf_lo(can)) + bf_lo(san);
                    const float h10 = (bf_lo(xs1) - st.x) * st.y * (1.f + bf_hi(ca)) + bf_hi(sa);
                    const float h11 = (bf_hi(xs1) - st.x) * st.y * (1.f + bf_hi(can)) + bf_hi(san);
                    st_ll2(g_h + b * 144 + cta * 4 + (g >> 1), tagw(pack_bf16(h00, h01), tag), tagw(pack_bf16(h10, h11), tag), qs);
                } else {
                    ulonglong2* d = (kind == 1 ? g_q + b * 1024 + cta * 8 : g_mod + b * 576 + (cta - NHCTA) * 8) + (g >> 1);
                    st_ll2(d, tagw(__byte_perm(sa, san, 0x5410), tag), tagw(__byte_perm(sa, san, 0x7632), tag), qs);
                    st_ll2(d + 4, tagw(__byte_perm(ca, can, 0x5410), tag), tagw(__byte_perm(ca, can, 0x7632), tag), qs);
                }
            }
            STAMP(j == 0 ? 1 : 3);
            HSTAMP(49 + j);
        }
        cbar(live);
        STAMP(4);
    }
    if (role == 1) {
        asm volatile("bar.sync 2, 64;" ::: "memory");
        if (lane == 0) {
            unsigned* ctr = &g_item[(ep & 1) * 32];
            uint32_t k = 0, spins = 0;
            while (true) {
                const uint32_t r = lds32v(sbar + SB_REQ);
                if (r == REQ_STOP) break;
                if (r != k) {
                    const uint32_t base = atomicAdd(ctr, r - k) + ncta - k;
                    for (; k != r; k++) sts32v(sbar + SB_ITEM + 4 * (k & 3), ((k + 1) << 16) | min(base + k, 0xFFFFu), 1);
                } else {
                    __nanosleep(100);
                    SPIN(spins, LIM_G);
                }
            }
        }
        return;
    }

    if (live || (role == 2 && (CFG_DRY & 2))) {
        const int r = lane & 7, mi = lane >> 3;
        const bool valid = (g < 4) && ((g >> 1) == (c >> 1));
        uint32_t koff[2][2], voff[2][4];
#pragma unroll
        for (int ps = 0; ps < 2; ps++) {
            const int half = (r >> 2) ^ ps;
            const int x = 2 * (r & 3) + half;
#pragma unroll
            for (int i = 0; i < 2; i++) koff[ps][i] = (2 * r + half) * 128 + (((4 * i + mi) ^ x) << 4);
#pragma unroll
            for (int mt = 0; mt < 4; mt++)
                voff[ps][mt] = 8192 + (2 * (8 * (mi >> 1) + r) + half) * 128 + (((2 * mt + (mi & 1)) ^ x) << 4);
        }
        uint32_t u = warp;
        {
            uint32_t qa[8][2];
            float acc[2][4][4];
            float m0 = -INFINITY, m1 = -INFINITY, lsum = 0.f;
#pragma unroll
            for (int s = 0; s < 8; s++) qa[s][0] = qa[s][1] = 0u;
#pragma unroll
            for (int a = 0; a < 2; a++)
#pragma unroll
                for (int b2 = 0; b2 < 4; b2++)
#pragma unroll
                    for (int i = 0; i < 4; i++) acc[a][b2][i] = 0.f;
            while (true) {
                uint32_t mlo, mhi, spins = 0;
                do {
                    const uint64_t meta = lds64v(sbar + SB_META + 8 * (u & 31));
                    mlo = __shfl_sync(0xffffffffu, (uint32_t)meta, 0);
                    mhi = __shfl_sync(0xffffffffu, (uint32_t)(meta >> 32), 0);
                    if (!live) { mlo = (u ? MF_END : MF_FIRST | MF_LAST) | u; mhi = 1u << 16; }
                    SPIN(spins, LIM_S);
                } while ((mlo & 0xFFFFu) != (u & 0xFFFFu));
                if (!(mlo & MF_END)) USTAMP(u, 1);
                if (mlo & (MF_FIRST | MF_END)) {
                    const bool end = mlo & MF_END;
                    if (end) STAMPW(27);
                    if (end) break;
                    const int slab = (mlo >> 16) & 127;
                    const ulonglong2* qp = g_q + ((slab >> 4) * 32 + (slab & 15) * 2 + (g & 1)) * 32 + c;
                    const int uu = (g >> 1) & 1;
                    uint32_t pend = (live && g < 4) ? 255u : 0u, n = 0;
                    while (true) {
                        ulonglong2 v[8];
#pragma unroll
                        for (int s = 0; s < 8; s++) v[s] = ld_ll2(qp + (4 * (uu ^ (s >> 2)) + (s & 3)) * 4, pend >> s & 1);
                        const uint32_t was = pend;
#pragma unroll
                        for (int s = 0; s < 8; s++)
                            if (was >> s & 1) {
                                qa[s][0] = (uint32_t)v[s].x; qa[s][1] = (uint32_t)v[s].y;
                                if (ll_ok(v[s], tag)) pend &= ~(1u << s);
                            }
                        if (!__any_sync(0xffffffffu, pend != 0)) break;
                        __nanosleep(200);
                        SPIN(n, LIM_G);
                    }
                    m0 = m1 = -INFINITY; lsum = 0.f;
#pragma unroll
                    for (int a = 0; a < 2; a++)
#pragma unroll
                        for (int b2 = 0; b2 < 4; b2++)
#pragma unroll
                            for (int i = 0; i < 4; i++) acc[a][b2][i] = 0.f;
                }
                const int slot = (mlo >> 27) & 15;
                USTAMP(u, 2);
                mbar_wait(full0 + 8 * slot, mlo >> 31, live);
                USTAMP(u, 3);
                const uint32_t base = ring + slot * SLOT;
                float s[4][4];
#pragma unroll
                for (int t = 0; t < 4; t++) {
                    s[t][0] = s[t][1] = s[t][2] = s[t][3] = 0.f;
#pragma unroll
                    for (int ps = 0; ps < 2; ps++)
#pragma unroll
                        for (int i = 0; i < 2; i++) {
                            uint32_t b0, b1, b2, b3;
                            ldsm4(base + t * 2048 + koff[ps][i], b0, b1, b2, b3);
                            mma16816(s[t], qa[ps * 4 + 2 * i][0], 0u, qa[ps * 4 + 2 * i][1], 0u, b0, b1);
                            mma16816(s[t], qa[ps * 4 + 2 * i + 1][0], 0u, qa[ps * 4 + 2 * i + 1][1], 0u, b2, b3);
                        }
                }
                float mx = -INFINITY;
#pragma unroll
                for (int t = 0; t < 4; t++) {
                    s[t][0] = valid ? s[t][0] * SCALE_LOG2 : -INFINITY;
                    s[t][1] = valid ? s[t][1] * SCALE_LOG2 : -INFINITY;
                    mx = fmaxf(mx, fmaxf(s[t][0], s[t][1]));
                }
                mx = fmaxf(mx, __shfl_xor_sync(0xffffffffu, mx, 1));
                mx = fmaxf(mx, __shfl_xor_sync(0xffffffffu, mx, 10));
                const float mx0 = __shfl_sync(0xffffffffu, mx, 0), mx1 = __shfl_sync(0xffffffffu, mx, 4);
                if (mx0 > m0 || mx1 > m1 || !live) {
                    const float n0 = fmaxf(m0, mx0), n1 = fmaxf(m1, mx1);
                    const float a0 = ex2(m0 - n0), a1 = ex2(m1 - n1);
                    m0 = n0; m1 = n1;
                    lsum *= (g & 1) ? a1 : a0;
#pragma unroll
                    for (int a = 0; a < 2; a++)
#pragma unroll
                        for (int b2 = 0; b2 < 4; b2++) {
                            acc[a][b2][0] *= a0; acc[a][b2][1] *= a1; acc[a][b2][2] *= a0; acc[a][b2][3] *= a1;
                        }
                }
                const float mh = (g & 1) ? m1 : m0;
                uint32_t pb[4];
#pragma unroll
                for (int t = 0; t < 4; t++) {
                    const float p0 = ex2(s[t][0] - mh), p1 = ex2(s[t][1] - mh);
                    lsum += p0 + p1;
                    pb[t] = pack_bf16(p0, p1);
                }
#pragma unroll
                for (int kk = 0; kk < 2; kk++)
#pragma unroll
                    for (int ps = 0; ps < 2; ps++)
#pragma unroll
                        for (int mt = 0; mt < 4; mt++) {
                            uint32_t a0, a1, a2, a3;
                            ldsm4t(base + kk * 4096 + voff[ps][mt], a0, a1, a2, a3);
                            mma16816(acc[ps][mt], a0, a1, a2, a3, pb[2 * kk], pb[2 * kk + 1]);
                        }
                __syncwarp();
                mbar_arrive(empty0 + 8 * slot, live && lane == 0);
                USTAMP(u, 4);

                if (mlo & MF_LAST) {
                    float l = lsum;
                    l += __shfl_xor_sync(0xffffffffu, l, 1);
                    l += __shfl_xor_sync(0xffffffffu, l, 10);
                    const float l0 = __shfl_sync(0xffffffffu, l, 0), l1 = __shfl_sync(0xffffffffu, l, 4);
                    const int cnt = (mhi >> 16) & 15;
                    ulonglong2* row = g_part + (size_t)(mhi & 2047) * (2 * 4 * 18);
#pragma unroll
                    for (int mt = 0; mt < 4; mt++)
#pragma unroll
                        for (int i = 0; i < 4; i++) acc[0][mt][i] += __shfl_xor_sync(0xffffffffu, acc[1][mt][i], 1);
                    if (cnt == 1) {
                        mbar_wait(sbar + SB_CLRB, 0, live);
                        ulonglong2* d = row + 2 * c * 18 + g;
#pragma unroll
                        for (int mt = 0; mt < 4; mt++)
#pragma unroll
                            for (int h = 0; h < 2; h++)
                                st_ll2(d + (h * 4 + (mt >> 1)) * 18 + (mt & 1) * 8, tagw(__float_as_uint(acc[0][mt][h]), tag),
                                       tagw(__float_as_uint(acc[0][mt][h + 2]), tag), live && c < 2);
                        st_ll2(row + lane * 18 + 16, tagw(__float_as_uint(lane < 4 ? m0 : m1), tag),
                               tagw(__float_as_uint(lane < 4 ? l0 : l1), tag), live && lane < 8);
                    } else {
                    const int entry = (mhi >> 13) & 7, mb = (mhi >> 20) & (NMB - 1);
                    const uint32_t gen = (mhi >> 22) & 255u;
                    {
                        uint32_t n = 0;
                        while (live && lds32v(sbar + SB_GEN + 4 * mb) != gen) SPIN(n, LIM_S);
                    }
                    const uint32_t dst = smrg + (mb * NCW + entry) * (MERGE_W * 4);
                    const uint32_t dl = dst + (c * 32 + g) * 8, qd = live && c < 2;
#pragma unroll
                    for (int mt = 0; mt < 4; mt++)
#pragma unroll
                        for (int h = 0; h < 2; h++)
                            sts64(dl + (h * 64 + mt * 8) * 8, __float_as_uint(acc[0][mt][h]), __float_as_uint(acc[0][mt][h + 2]), qd);
                    sts128(dst + 1024, __float_as_uint(m0), __float_as_uint(m1), __float_as_uint(l0), __float_as_uint(l1),
                           live && lane == 0);
                    __syncwarp();
                    uint32_t old;
                    asm volatile("{\n.reg .pred q;\nsetp.ne.u32 q, %2, 0;\nmov.u32 %0, 0;\n@q fence.acq_rel.cta;\n"
                                 "@q atom.shared.add.u32 %0, [%1], 1;\n@q fence.acq_rel.cta;\n}"
                                 : "=r"(old) : "r"(sbar + SB_CNT + 4 * mb), "r"((uint32_t)(live && lane == 0)) : "memory");
                    old = __shfl_sync(0xffffffffu, old, 0);
                    USTAMP(u, 5);
                    if ((int)old == cnt - 1) {
                        const uint32_t src = smrg + mb * NCW * (MERGE_W * 4);
                        float M0 = -INFINITY, M1 = -INFINITY;
#pragma unroll 1
                        for (int w = 0; w < cnt; w++) {
                            const float2 m = ldsf2(src + w * (MERGE_W * 4) + 1024);
                            M0 = fmaxf(M0, m.x); M1 = fmaxf(M1, m.y);
                        }
                        float o[2][4] = {{0.f, 0.f, 0.f, 0.f}, {0.f, 0.f, 0.f, 0.f}}, L0 = 0.f, L1 = 0.f;
#pragma unroll 1
                        for (int w = 0; w < cnt; w++) {
                            const uint32_t e = src + w * (MERGE_W * 4);
                            const float2 m = ldsf2(e + 1024), l = ldsf2(e + 1032);
                            const float sc0 = ex2(m.x - M0), sc1 = ex2(m.y - M1);
                            const float2 va = ldsf2(e + lane * 8), vb = ldsf2(e + 256 + lane * 8);
                            const float2 vc = ldsf2(e + 512 + lane * 8), vd = ldsf2(e + 768 + lane * 8);
                            o[0][0] += sc0 * va.x; o[0][1] += sc0 * va.y; o[0][2] += sc0 * vb.x; o[0][3] += sc0 * vb.y;
                            o[1][0] += sc1 * vc.x; o[1][1] += sc1 * vc.y; o[1][2] += sc1 * vd.x; o[1][3] += sc1 * vd.y;
                            L0 += sc0 * l.x; L1 += sc1 * l.y;
                        }
                        __syncwarp();
                        if (live && lane == 0) {
                            sts32v(sbar + SB_CNT + 4 * mb, 0u, 1);
                            asm volatile("fence.acq_rel.cta;" ::: "memory");
                            sts32v(sbar + SB_GEN + 4 * mb, (gen + 1) & 255u, 1);
                        }
                        mbar_wait(sbar + SB_CLRB, 0, live && (mhi >> 11 & 1));
#pragma unroll
                        for (int h = 0; h < 2; h++) {
                            ulonglong2* d = row + (h * 4 + (lane >> 4)) * 18 + (lane & 15);
                            st_ll2(d, tagw(__float_as_uint(o[h][0]), tag), tagw(__float_as_uint(o[h][1]), tag), live);
                            st_ll2(d + 36, tagw(__float_as_uint(o[h][2]), tag), tagw(__float_as_uint(o[h][3]), tag), live);
                        }
                        st_ll2(row + lane * 18 + 16, tagw(__float_as_uint(lane < 4 ? M0 : M1), tag),
                               tagw(__float_as_uint(lane < 4 ? L0 : L1), tag), live && lane < 8);
                    }
                    }
                }
                USTAMP(u, 6);
                u += NCW;
            }
        }
    }
    if (role == 1 || (live && cta >= NWORK)) return;

    const uint32_t s_b = sbar + SB_B, s_rr = smrg + SC_RR, s_gu = smrg + SC_H;
    if (!live) asm volatile("bar.sync 3, 96;" ::: "memory");
    if (role == 2) {
        uint32_t n = 0;
        while (lds32v(sbar + SB_FLAG2) == 0u) { __nanosleep(1000); SPIN(n, LIM_G); }
        if (cta < NRED) {
            float4* d = g_r + (size_t)cta * (NWORK * 16) + lane;
#pragma unroll 1
            for (int r = 0; r < 2; r++)
#pragma unroll 8
                for (int i = 0; i < NWORK * 16 / 32; i++) st_r4(d + (size_t)r * (NRED * NWORK * 16) + 32 * i, 0u, 0u, 0u, 0u, 1);
        }
        if (cta < NWORK) {
            ulonglong2* d = g_part + ((size_t)cta * RPS + JLATE) * (2 * 4 * 18) + lane;
#pragma unroll 6
            for (int i = 0; i < (PPS - JLATE) * 144 / 32; i++) st_r4(d + 32 * i, 0u, 0u, 0u, 0u, 1);
            st_r4(g_x1 + cta * 9 + lane, 0u, 0u, 0u, 0u, lane < 9);
            __syncwarp();
            if (lane == 0) asm volatile("fence.acq_rel.gpu;\nred.relaxed.gpu.global.add.u32 [%0], 1;" ::"l"(g_clr) : "memory");
        }
        if (lane == 0) {
            while (ld_acq(g_clr, 1) != tag * NWORK) { __nanosleep(1000); SPIN(n, LIM_G); }
            mbar_arrive(sbar + SB_CLRB, 1);
        }
    }
    __syncwarp();
    if (cta >= NWORK) return;
#pragma unroll 1
    for (int rep = (live || role == 2 || !(CFG_DRY & 4)) ? 1 : 0; rep < 2; rep++) {
        if (!live && !rep) {
            uint32_t n = 0;
            while (lds32v(sbar + SB_FLAG2) == 0u) { __nanosleep(1000); SPIN(n, LIM_G); }
        }
        if (!live && rep) {
            uint32_t n = 0;
            if (role == 2 || !(CFG_DRY & 4)) return;
            while (lds32v(sbar + SB_FLAG) == 0u) { __nanosleep(500); SPIN(n, LIM_G); }
        }
        int lane_o = lane, warp_o = warp;
        asm volatile("" : "+r"(lane_o), "+r"(warp_o));
        const int lane = lane_o, warp = warp_o, tid = warp * 32 + lane, g = lane >> 2, c = lane & 3;
        const int lrow = (lane & 7) + ((lane >> 4) & 1) * 8, cb1 = (lane >> 3) & 1;
        const uint32_t wsw = (((warp & 3) * 2 + cb1) ^ (lrow & 7)) << 4;
        auto reduce = [&](int round, float& sx, float& sy) {
            float4* src = g_r + (size_t)round * (NRED * NWORK * 16) + (size_t)cta * (NWORK * 16) + tid;
            uint4 v[8];
    #pragma unroll
            for (int i = 0; i < 8; i++) v[i] = make_uint4(0u, 0u, 0u, 0u);
            uint32_t pend = live ? 255u : 0u, n = 0;
            if (round ? CFG_PD : CFG_PD1) {
                const long long t0 = clock64();
                while (live && clock64() - t0 < (round ? CFG_PD : CFG_PD1)) {}
            }
            do {
    #pragma unroll
                for (int i = 0; i < 8; i++) ld_r4k(v[i], src + 256 * i, pend >> i & 1);
    #pragma unroll
                for (int i = 0; i < 8; i++)
                    if (v[i].x && v[i].y && v[i].z && v[i].w) pend &= ~(1u << i);
                SPIN(n, LIM_G);
            } while (__any_sync(0xffffffffu, pend != 0));
            float4 a = make_float4(0.f, 0.f, 0.f, 0.f);
    #pragma unroll
            for (int i = 0; i < 8; i++) {
                a.x += __uint_as_float(v[i].x); a.y += __uint_as_float(v[i].y);
                a.z += __uint_as_float(v[i].z); a.w += __uint_as_float(v[i].w);
            }
            a.x += __shfl_xor_sync(0xffffffffu, a.x, 16); a.y += __shfl_xor_sync(0xffffffffu, a.y, 16);
            a.z += __shfl_xor_sync(0xffffffffu, a.z, 16); a.w += __shfl_xor_sync(0xffffffffu, a.w, 16);
            sts128(s_rr + (warp * 64 + lane * 4) * 4, __float_as_uint(a.x), __float_as_uint(a.y), __float_as_uint(a.z),
                   __float_as_uint(a.w), live && lane < 16);
            cbar(live);
            sx = sy = 0.f;
            if (tid < 32) {
                const int bl = tid >> 3, pp = tid & 7;
                const uint32_t ra = s_rr + ((((2 * pp) & 7) * 2 + (bl >> 1)) * 4 + (pp >> 2) * 2 + (bl & 1)) * 4;
    #pragma unroll
                for (int w = 0; w < 8; w++) { sx += ldsf(ra + w * 256); sy += ldsf(ra + w * 256 + 32); }
            }
        };
        float4* const rdst = g_r + ((warp * 2 + (c >> 1)) * NWORK + cta) * 16 + g * 2 + (c & 1);
        uint32_t fin;
        {
            const ulonglong2* rows = g_part + ((size_t)(warp * 16 + (cta >> 3)) * RPS + (lane >> 4)) * (2 * 4 * 18) +
                                     (((cta >> 2) & 1) * 4 + (cta & 3)) * 18;
            uint32_t tpend = live ? (lane < 16 ? 0x7Fu : 0x3Fu) : 0u;
            float tM = NEG, tL = 0.f, tO0 = 0.f, tO1 = 0.f;
            ulonglong2 v[7], ml[7];
            WSTAMP(1);
            cbar(live);
            STAMP(43);
#pragma unroll
            for (int i = 0; i < 7; i++) {
                v[i] = ld_ll2(rows + i * (2 * 2 * 4 * 18) + (lane & 15), tpend >> i & 1);
                ml[i] = ld_ll2(rows + i * (2 * 2 * 4 * 18) + 16, tpend >> i & 1);
            }
            WSTAMP(2);
            fin = lds32v(sbar + SB_FIN);
            mbar_wait(sbar + SB_CLRB, 0, live);
            uint32_t n = 0;
            while (true) {
                float m[7], l[7], o0[7], o1[7];
                uint32_t np = tpend;
#pragma unroll
                for (int i = 0; i < 7; i++) {
                    const bool ok = (tpend >> i & 1) && ll_ok(v[i], tag) && ll_ok(ml[i], tag);
                    m[i] = ok ? __uint_as_float((uint32_t)ml[i].x) : NEG;
                    l[i] = ok ? __uint_as_float((uint32_t)ml[i].y) : 0.f;
                    o0[i] = ok ? __uint_as_float((uint32_t)v[i].x) : 0.f;
                    o1[i] = ok ? __uint_as_float((uint32_t)v[i].y) : 0.f;
                    if (ok) np &= ~(1u << i);
                }
                if (n == 0) WSTAMP(3);
                const bool more = __any_sync(0xffffffffu, np != 0);
                if (more || !live) {
#pragma unroll
                    for (int i = 0; i < 7; i++) {
                        ld_ll2k(v[i], rows + i * (2 * 2 * 4 * 18) + (lane & 15), np >> i & 1);
                        ld_ll2k(ml[i], rows + i * (2 * 2 * 4 * 18) + 16, np >> i & 1);
                    }
                }
                const float Mn = fmaxf(fmaxf(fmaxf(tM, m[0]), fmaxf(m[1], m[2])), fmaxf(fmaxf(m[3], m[4]), fmaxf(m[5], m[6])));
                const float a = ex2(tM - Mn);
                tM = Mn;
                tL *= a; tO0 *= a; tO1 *= a;
#pragma unroll
                for (int i = 0; i < 7; i++) {
                    const float b = ex2(m[i] - Mn);
                    tL += l[i] * b;
                    tO0 += o0[i] * b;
                    tO1 += o1[i] * b;
                }
                tpend = np;
                SPIN(n, LIM_G);
                if (!more) break;
            }
            WSTAMP(6);
            if (CFG_WH & 4) mbar_arrive(sbar + SB_T1, live && lane == 0);
            wait_pieces<3>(full0, fin, 0, live);
            uint32_t wa[5][2][4];
#pragma unroll
            for (int i = 0; i < 5; i++) {
                const int pl = min(2 * i + (warp >> 2), 8), pc = pl / 3;
                const uint32_t a = ring + piece_slot(fin, pc) * SLOT + (pl - 3 * pc) * 4096 + lrow * 128 + wsw;
                ldsm4t(a, wa[i][0][0], wa[i][0][1], wa[i][0][2], wa[i][0][3]);
                ldsm4t(a + 2048, wa[i][1][0], wa[i][1][1], wa[i][1][2], wa[i][1][3]);
            }
            {
                const float M2 = __shfl_xor_sync(0xffffffffu, tM, 16), L2 = __shfl_xor_sync(0xffffffffu, tL, 16);
                const float P0 = __shfl_xor_sync(0xffffffffu, tO0, 16), P1 = __shfl_xor_sync(0xffffffffu, tO1, 16);
                const float Mn = fmaxf(tM, M2);
                const float a = ex2(tM - Mn), b = ex2(M2 - Mn);
                const float inv = __fdividef(1.f, tL * a + L2 * b);
                const uint32_t ov = pack_bf16((tO0 * a + P0 * b) * inv, (tO1 * a + P1 * b) * inv);
                const uint32_t ob = s_b + (warp * 56 + (lane >> 3) * 16 + (lane & 7)) * 2;
                sts16(ob, lane < 16 ? (uint16_t)ov : (uint16_t)0, live && lane < 24);
                sts16(ob + 16, lane < 16 ? (uint16_t)(ov >> 16) : (uint16_t)0, live && lane < 24);
            }
            cbar(live);
            STAMP(14);
            const uint32_t bp = s_b + (g * 56 + 2 * c) * 2;
            const uint32_t b0 = lds32(bp), b1 = lds32(bp + 16), b2 = lds32(bp + 32), b3 = lds32(bp + 48);
#pragma unroll
            for (int i = 0; i < 5; i++) {
                float a4[4] = {0.f, 0.f, 0.f, 0.f};
                mma16816(a4, wa[i][0][0], wa[i][0][1], wa[i][0][2], wa[i][0][3], b0, b1);
                mma16816(a4, wa[i][1][0], wa[i][1][1], wa[i][1][2], wa[i][1][3], b2, b3);
                st_r4(rdst + i * (16 * NWORK * 16), nz(a4[0]), nz(a4[1]), nz(a4[2]), nz(a4[3]), live && warp + 8 * i < 36);
            }
            STAMP(7);
        }
        uint32_t xw;
        uint64_t gav, gbv;
        const uint64_t* gm = (const uint64_t*)(g_mod + ((cta & 1) * 4 + ((tid >> 3) & 3)) * 576 + (cta >> 1) * 4 + (tid & 3)) + ((tid >> 2) & 1);
        ulonglong2 sbv[5], cbv[5];
        {
            const uint32_t q = live && cta < NRED && tid < 32;
            const int b = (cta & 1) * 4 + ((tid >> 3) & 3), pp = tid & 7, mt = cta >> 1;
            xw = ldg4(p.x + b * DM + mt * 16 + 2 * pp, q);
            gav = ld_ll(gm, q); gbv = ld_ll(gm + 3 * 144 * 2, q);
#pragma unroll
            for (int i = 0; i < 5; i++) {
                const uint32_t q = live && lane + 32 * i < 144;
                sbv[i] = ld_ll2(g_mod + warp * 576 + 144 + lane + 32 * i, q);
                cbv[i] = ld_ll2(g_mod + warp * 576 + 288 + lane + 32 * i, q);
            }
        }
        float x1a = 0.f, x1b = 0.f;
        if (cta < NRED) {
            float sx, sy;
            reduce(0, sx, sy);
            if (tid < 32) {
                const int b = (cta & 1) * 4 + (tid >> 3), pp = tid & 7, mt = cta >> 1;
                uint32_t n = 0;
                while (live && ((uint32_t)(gav >> 32) != tag || (uint32_t)(gbv >> 32) != tag)) {
                    gav = ld_ll(gm, 1); gbv = ld_ll(gm + 3 * 144 * 2, 1);
                    SPIN(n, LIM_G);
                }
                x1a = bf_lo(xw) + bf_lo((uint32_t)gav) * sx;
                x1b = bf_hi(xw) + bf_hi((uint32_t)gav) * sy;
                st_ll((uint64_t*)(g_x1 + b * 144 + mt * 4 + (pp & 3)) + (pp >> 2), tagw(pack_bf16(x1a, x1b), tag), live);
            }
            STAMP(16);
        }
        float ga[5][4];
        {
            uint32_t wp[3];
#pragma unroll
            for (int k = 0; k < 3; k++) wp[k] = ring + piece_slot(fin, (cb1 ? 6 : 3) + k) * SLOT + lrow * 80 + (warp - k * 12) * 1280;
            const uint32_t w1 = warp < 4 ? wp[0] : wp[1];
            uint32_t fa[3][5][4];
            uint32_t sb[10], cb[10];
            {
                bool ok = true;
#pragma unroll
                for (int i = 0; i < 5; i++)
                    if (lane + 32 * i < 144) ok = ok && ll_ok(sbv[i], tag) && ll_ok(cbv[i], tag);
#pragma unroll
                for (int i = 0; i < 5; i++) {
                    sb[2 * i] = (uint32_t)sbv[i].x; sb[2 * i + 1] = (uint32_t)sbv[i].y;
                    cb[2 * i] = (uint32_t)cbv[i].x; cb[2 * i + 1] = (uint32_t)cbv[i].y;
                }
                if (live && !__all_sync(0xffffffffu, ok)) {
                    poll_row(g_mod + warp * 576 + 144, tag, lane, live, sb);
                    poll_row(g_mod + warp * 576 + 288, tag, lane, live, cb);
                }
            }
            wait_pieces<6>(full0, fin, 3, live);
            STAMP(19);
#pragma unroll
            for (int t = 0; t < 3; t++)
#pragma unroll
                for (int j = 0; j < 5; j++)
                    ldsm4t((t == 0 ? wp[0] : (t == 1 ? w1 : wp[1])) + t * 8 * 1280 + j * 16, fa[t][j][0], fa[t][j][1], fa[t][j][2], fa[t][j][3]);
            uint32_t w[10];
            poll_row(g_x1 + warp * 144, tag, lane, live, w);
            STAMP(8);
            float sum = 0.f;
#pragma unroll
            for (int i = 0; i < 5; i++)
                sum += (bf_lo(w[2 * i]) + bf_hi(w[2 * i])) + (bf_lo(w[2 * i + 1]) + bf_hi(w[2 * i + 1]));
#pragma unroll
            for (int o = 16; o; o >>= 1) sum += __shfl_xor_sync(0xffffffffu, sum, o);
            const float mean = sum * (1.f / DM);
            float var = 0.f;
#pragma unroll
            for (int i = 0; i < 5; i++)
                if (lane + 32 * i < 144) {
                    const float d0 = bf_lo(w[2 * i]) - mean, d1 = bf_hi(w[2 * i]) - mean;
                    const float d2 = bf_lo(w[2 * i + 1]) - mean, d3 = bf_hi(w[2 * i + 1]) - mean;
                    var += (d0 * d0 + d1 * d1) + (d2 * d2 + d3 * d3);
                }
#pragma unroll
            for (int o = 16; o; o >>= 1) var += __shfl_xor_sync(0xffffffffu, var, o);
            const float rstd = rsqrtf(var * (1.f / DM) + 1e-5f);
#pragma unroll
            for (int i = 0; i < 5; i++) {
                const int un = lane + 32 * i;
                const uint32_t d = s_c + (warp * INP + (un >> 2) * 16 + (un & 3) * 2) * 2;
#pragma unroll
                for (int e = 0; e < 2; e++) {
                    const uint32_t xx = w[2 * i + e], cc = cb[2 * i + e], ss = sb[2 * i + e];
                    sts32(d + 16 * e, pack_bf16((bf_lo(xx) - mean) * rstd * (1.f + bf_lo(cc)) + bf_lo(ss),
                                                (bf_hi(xx) - mean) * rstd * (1.f + bf_hi(cc)) + bf_hi(ss)), live && un < 144);
                }
            }
            uint32_t fb[2][5][4];
#pragma unroll
            for (int t = 3; t < 5; t++)
#pragma unroll
                for (int j = 0; j < 5; j++)
                    ldsm4t(wp[2] + (t == 4 && warp >= 4 ? 3 : t) * 8 * 1280 + j * 16, fb[t - 3][j][0], fb[t - 3][j][1], fb[t - 3][j][2], fb[t - 3][j][3]);
            cbar(live);
            STAMP(18);
            const uint32_t bp = s_c + (g * INP + 2 * c + warp * 16) * 2;
            uint32_t bb[5][2];
#pragma unroll
            for (int t = 0; t < 5; t++) {
                const bool on = t < 4 || warp < 4;
                bb[t][0] = on ? lds32(bp + t * 256) : 0u;
                bb[t][1] = on ? lds32(bp + t * 256 + 16) : 0u;
            }
#pragma unroll
            for (int j = 0; j < 5; j++) ga[j][0] = ga[j][1] = ga[j][2] = ga[j][3] = 0.f;
#pragma unroll
            for (int t = 0; t < 5; t++)
                if (t < 4 || warp < 4) {
#pragma unroll
                    for (int j = 0; j < 5; j++) {
                        if (t < 3) mma16816(ga[j], fa[t][j][0], fa[t][j][1], fa[t][j][2], fa[t][j][3], bb[t][0], bb[t][1]);
                        else mma16816(ga[j], fb[t - 3][j][0], fb[t - 3][j][1], fb[t - 3][j][2], fb[t - 3][j][3], bb[t][0], bb[t][1]);
                    }
                }
        }
#pragma unroll
        for (int j = 0; j < 5; j++)
            sts128(s_gu + ((warp * 5 + j) * 32 + lane) * 16, __float_as_uint(ga[j][0]), __float_as_uint(ga[j][1]),
                   __float_as_uint(ga[j][2]), __float_as_uint(ga[j][3]), live);
        uint32_t da[5][3][4];
        wait_pieces<3>(full0, fin, 9, live);
        STAMP(20);
#pragma unroll
        for (int i = 0; i < 5; i++) {
            const int pl = min(2 * i + (warp >> 2), 8), pc = pl / 3;
            const uint32_t a = ring + piece_slot(fin, 9 + pc) * SLOT + (pl - 3 * pc) * 5120 + wsw;
            ldsm4t(a + lrow * 128, da[i][0][0], da[i][0][1], da[i][0][2], da[i][0][3]);
            ldsm4t(a + lrow * 128 + 2048, da[i][1][0], da[i][1][1], da[i][1][2], da[i][1][3]);
            ldsm4t(a + (lrow & 7) * 128 + 4096, da[i][2][0], da[i][2][1], da[i][2][2], da[i][2][3]);
        }
        cbar(live);
        if (tid < 160) {
            float4 sm = make_float4(0.f, 0.f, 0.f, 0.f);
#pragma unroll
            for (int q = 0; q < 8; q++) {
                uint32_t r0, r1, r2, r3;
                asm volatile("ld.shared.v4.b32 {%0, %1, %2, %3}, [%4];" : "=r"(r0), "=r"(r1), "=r"(r2), "=r"(r3)
                             : "r"(s_gu + (q * 160 + tid) * 16) : "memory");
                sm.x += __uint_as_float(r0); sm.y += __uint_as_float(r1); sm.z += __uint_as_float(r2); sm.w += __uint_as_float(r3);
            }
            const float i0 = 1.5957691216057308f * (sm.x + 0.044715f * sm.x * sm.x * sm.x);
            const float i1 = 1.5957691216057308f * (sm.y + 0.044715f * sm.y * sm.y * sm.y);
            const uint32_t v = pack_bf16(__fdividef(sm.x, 1.f + __expf(-i0)) * sm.z, __fdividef(sm.y, 1.f + __expf(-i1)) * sm.w);
            const int k = warp * 8 + g - ((cta * 36) & 7);
            const uint32_t q = live && k >= 0 && k < 36;
            sts16(s_b + (2 * c * 56 + k) * 2, (uint16_t)v, q);
            sts16(s_b + ((2 * c + 1) * 56 + k) * 2, (uint16_t)(v >> 16), q);
        }
        cbar(live);
        STAMP(9);
        {
            const uint32_t bp = s_b + (g * 56 + 2 * c) * 2;
            uint32_t bb[3][2];
#pragma unroll
            for (int ks = 0; ks < 3; ks++) { bb[ks][0] = lds32(bp + ks * 32); bb[ks][1] = lds32(bp + ks * 32 + 16); }
#pragma unroll
            for (int i = 0; i < 5; i++) {
                float a4[4] = {0.f, 0.f, 0.f, 0.f};
#pragma unroll
                for (int ks = 0; ks < 3; ks++) mma16816(a4, da[i][ks][0], da[i][ks][1], da[i][ks][2], da[i][ks][3], bb[ks][0], bb[ks][1]);
                st_r4(rdst + (NRED * NWORK * 16) + i * (16 * NWORK * 16), nz(a4[0]), nz(a4[1]), nz(a4[2]), nz(a4[3]), live && warp + 8 * i < 36);
            }
        }
        STAMP(10);
        if (cta < NRED) {
            float sx, sy;
            reduce(1, sx, sy);
            if (tid < 32 && live) {
                const int b = (cta & 1) * 4 + (tid >> 3), pp = tid & 7, mt = cta >> 1;
                *(uint32_t*)(p.out + b * DM + mt * 16 + 2 * pp) = pack_bf16(x1a + bf_lo((uint32_t)gbv) * sx, x1b + bf_hi((uint32_t)gbv) * sy);
            }
            STAMP(11);
        }
    }
    if (live && cta == 0 && tid == 0) g_epoch[0] = ep + 1;
}

typedef CUresult (*EncodeFn)(CUtensorMap*, CUtensorMapDataType, cuuint32_t, void*, const cuuint64_t*, const cuuint64_t*,
                             const cuuint32_t*, const cuuint32_t*, CUtensorMapInterleave, CUtensorMapSwizzle,
                             CUtensorMapL2promotion, CUtensorMapFloatOOBfill);

void make_map(EncodeFn fn, CUtensorMap* m, const void* ptr, int rank, const uint64_t* dims_, const uint64_t* strides_,
              const uint32_t* box_, CUtensorMapSwizzle sw) {
    cuuint64_t dims[4], strides[3];
    cuuint32_t box[4], es[4] = {1, 1, 1, 1};
    for (int i = 0; i < rank; i++) { dims[i] = dims_[i]; box[i] = box_[i]; }
    for (int i = 0; i + 1 < rank; i++) strides[i] = strides_[i];
    fn(m, CU_TENSOR_MAP_DATA_TYPE_BFLOAT16, rank, const_cast<void*>(ptr), dims, strides, box, es,
       CU_TENSOR_MAP_INTERLEAVE_NONE, sw, CU_TENSOR_MAP_L2_PROMOTION_L2_128B, CU_TENSOR_MAP_FLOAT_OOB_FILL_NONE);
}

}

extern "C" void kernel_launch(void* const* d_in, const int* in_sizes, int n_in, void* d_out, int out_size) {
    static EncodeFn fn = nullptr;
    static int nsm = 0;
    if (!fn) {
        cudaDriverEntryPointQueryResult qres;
        void* f = nullptr;
        cudaGetDriverEntryPoint("cuTensorMapEncodeTiled", &f, cudaEnableDefault, &qres);
        fn = (EncodeFn)f;
        int dev = 0;
        cudaGetDevice(&dev);
        cudaDeviceGetAttribute(&nsm, cudaDevAttrMultiProcessorCount, dev);
        cudaFuncSetAttribute(fused_kernel, cudaFuncAttributeMaxDynamicSharedMemorySize, SM_TOTAL);
    }
    CUtensorMap mK, mV, mWo, mG, mU, mD, mQ, mM, mMh;
    {
        const uint64_t d[2] = {64, (uint64_t)NSLAB * SK * 2}, s[1] = {128};
        const uint32_t b[2] = {64, 64};
        make_map(fn, &mK, d_in[1], 2, d, s, b, CU_TENSOR_MAP_SWIZZLE_128B);
        make_map(fn, &mV, d_in[2], 2, d, s, b, CU_TENSOR_MAP_SWIZZLE_128B);
    }
    {
        const uint64_t d[3] = {64, 4096, 9}, s[2] = {DM * 2, 128};
        const uint32_t b[3] = {64, 32, 3};
        make_map(fn, &mWo, d_in[4], 3, d, s, b, CU_TENSOR_MAP_SWIZZLE_128B);
        const uint64_t d2[3] = {64, FF, 9};
        const uint32_t b2[3] = {64, 40, 3};
        make_map(fn, &mD, d_in[8], 3, d2, s, b2, CU_TENSOR_MAP_SWIZZLE_128B);
    }
    {
        const uint64_t d[3] = {FF, 192, 3}, s[2] = {FF * 2, 192ull * FF * 2};
        const uint32_t b[3] = {40, 192, 1};
        make_map(fn, &mG, d_in[6], 3, d, s, b, CU_TENSOR_MAP_SWIZZLE_NONE);
        make_map(fn, &mU, d_in[7], 3, d, s, b, CU_TENSOR_MAP_SWIZZLE_NONE);
    }
    {
        const uint64_t d[3] = {4096, 192, 3}, s[2] = {4096 * 2, 192ull * 4096 * 2};
        const uint32_t b[3] = {32, 192, 3};
        make_map(fn, &mQ, d_in[3], 3, d, s, b, CU_TENSOR_MAP_SWIZZLE_64B);
        const uint64_t d2[3] = {6 * DM, 192, 3}, s2[2] = {6 * DM * 2, 192ull * 6 * DM * 2};
        make_map(fn, &mM, d_in[10], 3, d2, s2, b, CU_TENSOR_MAP_SWIZZLE_64B);
        const uint32_t b2[3] = {16, 192, 3};
        make_map(fn, &mMh, d_in[10], 3, d2, s2, b2, CU_TENSOR_MAP_SWIZZLE_32B);
    }
    Params p;
    p.x = (const __nv_bfloat16*)d_in[0];
    p.c = (const __nv_bfloat16*)d_in[9];
    p.wq = (const __nv_bfloat16*)d_in[3];
    p.wmod = (const __nv_bfloat16*)d_in[10];
    p.wdown = (const __nv_bfloat16*)d_in[8];
    p.out = (__nv_bfloat16*)d_out;
    int grid = nsm < 132 ? nsm : 132;
    fused_kernel<<<grid, NTHREADS, SM_TOTAL>>>(mK, mV, mWo, mG, mU, mD, mQ, mM, mMh, p);
}
```
